```python
import torch

def _softmax(x, axis=-1):
    return torch.softmax(x, dim=axis)
def _gelu(x):
    return torch.nn.functional.gelu(x, approximate="tanh")
def _silu(x):
    return torch.nn.functional.silu(x)
def _sigmoid(x):
    return torch.sigmoid(x)
def _layernorm(x, axis=-1, eps=1e-5):
    m = x.mean(dim=axis, keepdim=True)
    v = x.var(dim=axis, keepdim=True, unbiased=False)
    return (x - m) / torch.sqrt(v + eps)
def _scatter_add(tgt, idx, src, axis=0):
    return tgt.clone().index_add_(axis, idx, src)
def _segment_sum(src, seg, n):
    out = torch.zeros((n,) + src.shape[1:], dtype=src.dtype)
    return out.index_add_(0, seg, src)
def _pad(x, pw):
    flat = tuple(v for pair in reversed(pw) for v in pair)
    return torch.nn.functional.pad(x, flat)

kernel_name = 'recurrent_scan__sliding_block__glu_gated_swiglu__prompt'

def setup_inputs():

    _w = (lambda a: (lambda t: t.to(torch.bfloat16) if t.is_floating_point() else t)(torch.as_tensor(a)))
    def _A_setup():
        B, S, D = 1, 2048, 448
        return {
            "x": _w((lambda *s: torch.randn(*s, dtype=torch.bfloat16) * 0.05)(B, S, D)),
            "wqkv": _w((lambda *s: torch.randn(*s, dtype=torch.bfloat16) * 0.2)(D, 3 * D)),
            "wo": _w((lambda *s: torch.randn(*s, dtype=torch.bfloat16) * 0.2)(D, D)),
        }
    _A_in = _A_setup()

    def _B_setup():
        B, S, D, F = 1, 2048, 448, 1792
        return {
            "x": _w((lambda *s: torch.randn(*s, dtype=torch.bfloat16) * 0.05)(B, S, D)),
            "w1": _w((lambda *s: torch.randn(*s, dtype=torch.bfloat16) * 0.1)(D, F) * (2.0 / D) ** 0.5),
            "w3": _w((lambda *s: torch.randn(*s, dtype=torch.bfloat16) * 0.1)(D, F) * (2.0 / D) ** 0.5),
            "w2": _w((lambda *s: torch.randn(*s, dtype=torch.bfloat16) * 0.1)(F, D) * (2.0 / F) ** 0.5),
        }
    _B_in = _B_setup()

    return {
        "A_x": _A_in["x"],
        "A_wqkv": _A_in["wqkv"],
        "A_wo": _A_in["wo"],
        "B_x": _B_in["x"],
        "B_w1": _B_in["w1"],
        "B_w3": _B_in["w3"],
        "B_w2": _B_in["w2"],
    }

def reference(A_x, A_wqkv, A_wo, B_x, B_w1, B_w3, B_w2):
    def _A_ref(x, wqkv, wo):
        B, S, D = x.shape
        H = 16; Dh = D // H; W = 256
        qkv = (lambda x, *d: x.permute(*d))((x @ wqkv).reshape(B, S, 3, H, Dh), 2, 0, 3, 1, 4)
        q, k, v = qkv[0], qkv[1], qkv[2]
        scores = torch.einsum("bhqd,bhkd->bhqk", q, k) * (Dh ** -0.5)
        idx = torch.arange(S)
        mask = (idx[:, None] - idx[None, :] >= 0) & (idx[:, None] - idx[None, :] < W)
        scores = torch.where(mask[None, None], scores, -1e9)
        p = _softmax(scores, axis=-1)
        o = torch.einsum("bhqk,bhkd->bhqd", p, v)
        return (lambda x, *d: x.permute(*d))(o, 0, 2, 1, 3).reshape(B, S, D) @ wo

    def _B_ref(x, w1, w3, w2):
        gate = torch.einsum("bsd,df->bsf", x, w1)
        up = torch.einsum("bsd,df->bsf", x, w3)
        h = _silu(gate) * up
        out = torch.einsum("bsf,fd->bsd", h, w2)
        return out

    x = A_x
    xn = _layernorm(x, axis=-1)
    s = _A_ref(xn, A_wqkv, A_wo)
    g = _silu(_B_ref(xn, B_w1, B_w3, B_w2))
    return x + s * g
```

```cpp
#include <cuda_runtime.h>
#include <cuda_bf16.h>
#include <cuda.h>
#include <stdint.h>

namespace {

template <int TB> __device__ __forceinline__ void wgmma_ss_n128(float (&d)[64], uint32_t alo, int oa, uint32_t ha, uint32_t blo, int ob, uint32_t hb, int scale_d) {
    asm volatile("{\n.reg .pred p;\n.reg .b32 ta, tb;\n.reg .b64 da, db;\nsetp.ne.b32 p, %70, 0;\n"
        "add.u32 ta, %64, %65;\nadd.u32 tb, %67, %68;\nmov.b64 da, {ta, %66};\nmov.b64 db, {tb, %69};\n"
        "wgmma.mma_async.sync.aligned.m64n128k16.f32.bf16.bf16 {%0, %1, %2, %3, %4, %5, %6, %7, %8, %9, %10, %11, %12, %13, %14, %15, %16, %17, %18, %19, %20, %21, %22, %23, %24, %25, %26, %27, %28, %29, %30, %31, %32, %33, %34, %35, %36, %37, %38, %39, %40, %41, %42, %43, %44, %45, %46, %47, %48, %49, %50, %51, %52, %53, %54, %55, %56, %57, %58, %59, %60, %61, %62, %63}, da, db, p, 1, 1, 0, %71;\n}\n"
        : "+f"(d[0]), "+f"(d[1]), "+f"(d[2]), "+f"(d[3]), "+f"(d[4]), "+f"(d[5]), "+f"(d[6]), "+f"(d[7]), "+f"(d[8]), "+f"(d[9]), "+f"(d[10]), "+f"(d[11]), "+f"(d[12]), "+f"(d[13]), "+f"(d[14]), "+f"(d[15]), "+f"(d[16]), "+f"(d[17]), "+f"(d[18]), "+f"(d[19]), "+f"(d[20]), "+f"(d[21]), "+f"(d[22]), "+f"(d[23]), "+f"(d[24]), "+f"(d[25]), "+f"(d[26]), "+f"(d[27]), "+f"(d[28]), "+f"(d[29]), "+f"(d[30]), "+f"(d[31]), "+f"(d[32]), "+f"(d[33]), "+f"(d[34]), "+f"(d[35]), "+f"(d[36]), "+f"(d[37]), "+f"(d[38]), "+f"(d[39]), "+f"(d[40]), "+f"(d[41]), "+f"(d[42]), "+f"(d[43]), "+f"(d[44]), "+f"(d[45]), "+f"(d[46]), "+f"(d[47]), "+f"(d[48]), "+f"(d[49]), "+f"(d[50]), "+f"(d[51]), "+f"(d[52]), "+f"(d[53]), "+f"(d[54]), "+f"(d[55]), "+f"(d[56]), "+f"(d[57]), "+f"(d[58]), "+f"(d[59]), "+f"(d[60]), "+f"(d[61]), "+f"(d[62]), "+f"(d[63])
        : "r"(alo), "r"(oa), "r"(ha), "r"(blo), "r"(ob), "r"(hb), "r"(scale_d), "n"(TB));
}

template <int TB> __device__ __forceinline__ void wgmma_ss_n112(float (&d)[56], uint32_t alo, int oa, uint32_t ha, uint32_t blo, int ob, uint32_t hb, int scale_d) {
    asm volatile("{\n.reg .pred p;\n.reg .b32 ta, tb;\n.reg .b64 da, db;\nsetp.ne.b32 p, %62, 0;\n"
        "add.u32 ta, %56, %57;\nadd.u32 tb, %59, %60;\nmov.b64 da, {ta, %58};\nmov.b64 db, {tb, %61};\n"
        "wgmma.mma_async.sync.aligned.m64n112k16.f32.bf16.bf16 {%0, %1, %2, %3, %4, %5, %6, %7, %8, %9, %10, %11, %12, %13, %14, %15, %16, %17, %18, %19, %20, %21, %22, %23, %24, %25, %26, %27, %28, %29, %30, %31, %32, %33, %34, %35, %36, %37, %38, %39, %40, %41, %42, %43, %44, %45, %46, %47, %48, %49, %50, %51, %52, %53, %54, %55}, da, db, p, 1, 1, 0, %63;\n}\n"
        : "+f"(d[0]), "+f"(d[1]), "+f"(d[2]), "+f"(d[3]), "+f"(d[4]), "+f"(d[5]), "+f"(d[6]), "+f"(d[7]), "+f"(d[8]), "+f"(d[9]), "+f"(d[10]), "+f"(d[11]), "+f"(d[12]), "+f"(d[13]), "+f"(d[14]), "+f"(d[15]), "+f"(d[16]), "+f"(d[17]), "+f"(d[18]), "+f"(d[19]), "+f"(d[20]), "+f"(d[21]), "+f"(d[22]), "+f"(d[23]), "+f"(d[24]), "+f"(d[25]), "+f"(d[26]), "+f"(d[27]), "+f"(d[28]), "+f"(d[29]), "+f"(d[30]), "+f"(d[31]), "+f"(d[32]), "+f"(d[33]), "+f"(d[34]), "+f"(d[35]), "+f"(d[36]), "+f"(d[37]), "+f"(d[38]), "+f"(d[39]), "+f"(d[40]), "+f"(d[41]), "+f"(d[42]), "+f"(d[43]), "+f"(d[44]), "+f"(d[45]), "+f"(d[46]), "+f"(d[47]), "+f"(d[48]), "+f"(d[49]), "+f"(d[50]), "+f"(d[51]), "+f"(d[52]), "+f"(d[53]), "+f"(d[54]), "+f"(d[55])
        : "r"(alo), "r"(oa), "r"(ha), "r"(blo), "r"(ob), "r"(hb), "r"(scale_d), "n"(TB));
}

template <int TB> __device__ __forceinline__ void wgmma_ss_n64(float (&d)[32], uint32_t alo, int oa, uint32_t ha, uint32_t blo, int ob, uint32_t hb, int scale_d) {
    asm volatile("{\n.reg .pred p;\n.reg .b32 ta, tb;\n.reg .b64 da, db;\nsetp.ne.b32 p, %38, 0;\n"
        "add.u32 ta, %32, %33;\nadd.u32 tb, %35, %36;\nmov.b64 da, {ta, %34};\nmov.b64 db, {tb, %37};\n"
        "wgmma.mma_async.sync.aligned.m64n64k16.f32.bf16.bf16 {%0, %1, %2, %3, %4, %5, %6, %7, %8, %9, %10, %11, %12, %13, %14, %15, %16, %17, %18, %19, %20, %21, %22, %23, %24, %25, %26, %27, %28, %29, %30, %31}, da, db, p, 1, 1, 0, %39;\n}\n"
        : "+f"(d[0]), "+f"(d[1]), "+f"(d[2]), "+f"(d[3]), "+f"(d[4]), "+f"(d[5]), "+f"(d[6]), "+f"(d[7]), "+f"(d[8]), "+f"(d[9]), "+f"(d[10]), "+f"(d[11]), "+f"(d[12]), "+f"(d[13]), "+f"(d[14]), "+f"(d[15]), "+f"(d[16]), "+f"(d[17]), "+f"(d[18]), "+f"(d[19]), "+f"(d[20]), "+f"(d[21]), "+f"(d[22]), "+f"(d[23]), "+f"(d[24]), "+f"(d[25]), "+f"(d[26]), "+f"(d[27]), "+f"(d[28]), "+f"(d[29]), "+f"(d[30]), "+f"(d[31])
        : "r"(alo), "r"(oa), "r"(ha), "r"(blo), "r"(ob), "r"(hb), "r"(scale_d), "n"(TB));
}

template <int TB> __device__ __forceinline__ void wgmma_ss_n56(float (&d)[28], uint32_t alo, int oa, uint32_t ha, uint32_t blo, int ob, uint32_t hb, int scale_d) {
    asm volatile("{\n.reg .pred p;\n.reg .b32 ta, tb;\n.reg .b64 da, db;\nsetp.ne.b32 p, %34, 0;\n"
        "add.u32 ta, %28, %29;\nadd.u32 tb, %31, %32;\nmov.b64 da, {ta, %30};\nmov.b64 db, {tb, %33};\n"
        "wgmma.mma_async.sync.aligned.m64n56k16.f32.bf16.bf16 {%0, %1, %2, %3, %4, %5, %6, %7, %8, %9, %10, %11, %12, %13, %14, %15, %16, %17, %18, %19, %20, %21, %22, %23, %24, %25, %26, %27}, da, db, p, 1, 1, 0, %35;\n}\n"
        : "+f"(d[0]), "+f"(d[1]), "+f"(d[2]), "+f"(d[3]), "+f"(d[4]), "+f"(d[5]), "+f"(d[6]), "+f"(d[7]), "+f"(d[8]), "+f"(d[9]), "+f"(d[10]), "+f"(d[11]), "+f"(d[12]), "+f"(d[13]), "+f"(d[14]), "+f"(d[15]), "+f"(d[16]), "+f"(d[17]), "+f"(d[18]), "+f"(d[19]), "+f"(d[20]), "+f"(d[21]), "+f"(d[22]), "+f"(d[23]), "+f"(d[24]), "+f"(d[25]), "+f"(d[26]), "+f"(d[27])
        : "r"(alo), "r"(oa), "r"(ha), "r"(blo), "r"(ob), "r"(hb), "r"(scale_d), "n"(TB));
}

template <int TB> __device__ __forceinline__ void wgmma_ssz_n128(float (&d)[64], uint32_t alo, int oa, uint32_t ha, uint32_t blo, int ob, uint32_t hb) {
    asm volatile("{\n.reg .pred p;\n.reg .b32 ta, tb;\n.reg .b64 da, db;\nsetp.ne.b32 p, 0, 0;\n"
        "add.u32 ta, %64, %65;\nadd.u32 tb, %67, %68;\nmov.b64 da, {ta, %66};\nmov.b64 db, {tb, %69};\n"
        "wgmma.mma_async.sync.aligned.m64n128k16.f32.bf16.bf16 {%0, %1, %2, %3, %4, %5, %6, %7, %8, %9, %10, %11, %12, %13, %14, %15, %16, %17, %18, %19, %20, %21, %22, %23, %24, %25, %26, %27, %28, %29, %30, %31, %32, %33, %34, %35, %36, %37, %38, %39, %40, %41, %42, %43, %44, %45, %46, %47, %48, %49, %50, %51, %52, %53, %54, %55, %56, %57, %58, %59, %60, %61, %62, %63}, da, db, p, 1, 1, 0, %70;\n}\n"
        : "=f"(d[0]), "=f"(d[1]), "=f"(d[2]), "=f"(d[3]), "=f"(d[4]), "=f"(d[5]), "=f"(d[6]), "=f"(d[7]), "=f"(d[8]), "=f"(d[9]), "=f"(d[10]), "=f"(d[11]), "=f"(d[12]), "=f"(d[13]), "=f"(d[14]), "=f"(d[15]), "=f"(d[16]), "=f"(d[17]), "=f"(d[18]), "=f"(d[19]), "=f"(d[20]), "=f"(d[21]), "=f"(d[22]), "=f"(d[23]), "=f"(d[24]), "=f"(d[25]), "=f"(d[26]), "=f"(d[27]), "=f"(d[28]), "=f"(d[29]), "=f"(d[30]), "=f"(d[31]), "=f"(d[32]), "=f"(d[33]), "=f"(d[34]), "=f"(d[35]), "=f"(d[36]), "=f"(d[37]), "=f"(d[38]), "=f"(d[39]), "=f"(d[40]), "=f"(d[41]), "=f"(d[42]), "=f"(d[43]), "=f"(d[44]), "=f"(d[45]), "=f"(d[46]), "=f"(d[47]), "=f"(d[48]), "=f"(d[49]), "=f"(d[50]), "=f"(d[51]), "=f"(d[52]), "=f"(d[53]), "=f"(d[54]), "=f"(d[55]), "=f"(d[56]), "=f"(d[57]), "=f"(d[58]), "=f"(d[59]), "=f"(d[60]), "=f"(d[61]), "=f"(d[62]), "=f"(d[63])
        : "r"(alo), "r"(oa), "r"(ha), "r"(blo), "r"(ob), "r"(hb), "n"(TB));
}

template <int TB> __device__ __forceinline__ void wgmma_ssz_n112(float (&d)[56], uint32_t alo, int oa, uint32_t ha, uint32_t blo, int ob, uint32_t hb) {
    asm volatile("{\n.reg .pred p;\n.reg .b32 ta, tb;\n.reg .b64 da, db;\nsetp.ne.b32 p, 0, 0;\n"
        "add.u32 ta, %56, %57;\nadd.u32 tb, %59, %60;\nmov.b64 da, {ta, %58};\nmov.b64 db, {tb, %61};\n"
        "wgmma.mma_async.sync.aligned.m64n112k16.f32.bf16.bf16 {%0, %1, %2, %3, %4, %5, %6, %7, %8, %9, %10, %11, %12, %13, %14, %15, %16, %17, %18, %19, %20, %21, %22, %23, %24, %25, %26, %27, %28, %29, %30, %31, %32, %33, %34, %35, %36, %37, %38, %39, %40, %41, %42, %43, %44, %45, %46, %47, %48, %49, %50, %51, %52, %53, %54, %55}, da, db, p, 1, 1, 0, %62;\n}\n"
        : "=f"(d[0]), "=f"(d[1]), "=f"(d[2]), "=f"(d[3]), "=f"(d[4]), "=f"(d[5]), "=f"(d[6]), "=f"(d[7]), "=f"(d[8]), "=f"(d[9]), "=f"(d[10]), "=f"(d[11]), "=f"(d[12]), "=f"(d[13]), "=f"(d[14]), "=f"(d[15]), "=f"(d[16]), "=f"(d[17]), "=f"(d[18]), "=f"(d[19]), "=f"(d[20]), "=f"(d[21]), "=f"(d[22]), "=f"(d[23]), "=f"(d[24]), "=f"(d[25]), "=f"(d[26]), "=f"(d[27]), "=f"(d[28]), "=f"(d[29]), "=f"(d[30]), "=f"(d[31]), "=f"(d[32]), "=f"(d[33]), "=f"(d[34]), "=f"(d[35]), "=f"(d[36]), "=f"(d[37]), "=f"(d[38]), "=f"(d[39]), "=f"(d[40]), "=f"(d[41]), "=f"(d[42]), "=f"(d[43]), "=f"(d[44]), "=f"(d[45]), "=f"(d[46]), "=f"(d[47]), "=f"(d[48]), "=f"(d[49]), "=f"(d[50]), "=f"(d[51]), "=f"(d[52]), "=f"(d[53]), "=f"(d[54]), "=f"(d[55])
        : "r"(alo), "r"(oa), "r"(ha), "r"(blo), "r"(ob), "r"(hb), "n"(TB));
}

template <int TB> __device__ __forceinline__ void wgmma_ssz_n64(float (&d)[32], uint32_t alo, int oa, uint32_t ha, uint32_t blo, int ob, uint32_t hb) {
    asm volatile("{\n.reg .pred p;\n.reg .b32 ta, tb;\n.reg .b64 da, db;\nsetp.ne.b32 p, 0, 0;\n"
        "add.u32 ta, %32, %33;\nadd.u32 tb, %35, %36;\nmov.b64 da, {ta, %34};\nmov.b64 db, {tb, %37};\n"
        "wgmma.mma_async.sync.aligned.m64n64k16.f32.bf16.bf16 {%0, %1, %2, %3, %4, %5, %6, %7, %8, %9, %10, %11, %12, %13, %14, %15, %16, %17, %18, %19, %20, %21, %22, %23, %24, %25, %26, %27, %28, %29, %30, %31}, da, db, p, 1, 1, 0, %38;\n}\n"
        : "=f"(d[0]), "=f"(d[1]), "=f"(d[2]), "=f"(d[3]), "=f"(d[4]), "=f"(d[5]), "=f"(d[6]), "=f"(d[7]), "=f"(d[8]), "=f"(d[9]), "=f"(d[10]), "=f"(d[11]), "=f"(d[12]), "=f"(d[13]), "=f"(d[14]), "=f"(d[15]), "=f"(d[16]), "=f"(d[17]), "=f"(d[18]), "=f"(d[19]), "=f"(d[20]), "=f"(d[21]), "=f"(d[22]), "=f"(d[23]), "=f"(d[24]), "=f"(d[25]), "=f"(d[26]), "=f"(d[27]), "=f"(d[28]), "=f"(d[29]), "=f"(d[30]), "=f"(d[31])
        : "r"(alo), "r"(oa), "r"(ha), "r"(blo), "r"(ob), "r"(hb), "n"(TB));
}

template <int TB> __device__ __forceinline__ void wgmma_ssz_n56(float (&d)[28], uint32_t alo, int oa, uint32_t ha, uint32_t blo, int ob, uint32_t hb) {
    asm volatile("{\n.reg .pred p;\n.reg .b32 ta, tb;\n.reg .b64 da, db;\nsetp.ne.b32 p, 0, 0;\n"
        "add.u32 ta, %28, %29;\nadd.u32 tb, %31, %32;\nmov.b64 da, {ta, %30};\nmov.b64 db, {tb, %33};\n"
        "wgmma.mma_async.sync.aligned.m64n56k16.f32.bf16.bf16 {%0, %1, %2, %3, %4, %5, %6, %7, %8, %9, %10, %11, %12, %13, %14, %15, %16, %17, %18, %19, %20, %21, %22, %23, %24, %25, %26, %27}, da, db, p, 1, 1, 0, %34;\n}\n"
        : "=f"(d[0]), "=f"(d[1]), "=f"(d[2]), "=f"(d[3]), "=f"(d[4]), "=f"(d[5]), "=f"(d[6]), "=f"(d[7]), "=f"(d[8]), "=f"(d[9]), "=f"(d[10]), "=f"(d[11]), "=f"(d[12]), "=f"(d[13]), "=f"(d[14]), "=f"(d[15]), "=f"(d[16]), "=f"(d[17]), "=f"(d[18]), "=f"(d[19]), "=f"(d[20]), "=f"(d[21]), "=f"(d[22]), "=f"(d[23]), "=f"(d[24]), "=f"(d[25]), "=f"(d[26]), "=f"(d[27])
        : "r"(alo), "r"(oa), "r"(ha), "r"(blo), "r"(ob), "r"(hb), "n"(TB));
}

template <int TB> __device__ __forceinline__ void wgmma_rs_n64(float (&d)[32], uint32_t a0, uint32_t a1, uint32_t a2, uint32_t a3, uint32_t blo, int ob, uint32_t hb, int scale_d) {
    asm volatile("{\n.reg .pred p;\n.reg .b32 tb;\n.reg .b64 db;\nsetp.ne.b32 p, %39, 0;\n"
        "add.u32 tb, %36, %37;\nmov.b64 db, {tb, %38};\n"
        "wgmma.mma_async.sync.aligned.m64n64k16.f32.bf16.bf16 {%0, %1, %2, %3, %4, %5, %6, %7, %8, %9, %10, %11, %12, %13, %14, %15, %16, %17, %18, %19, %20, %21, %22, %23, %24, %25, %26, %27, %28, %29, %30, %31}, {%32, %33, %34, %35}, db, p, 1, 1, %40;\n}\n"
        : "+f"(d[0]), "+f"(d[1]), "+f"(d[2]), "+f"(d[3]), "+f"(d[4]), "+f"(d[5]), "+f"(d[6]), "+f"(d[7]), "+f"(d[8]), "+f"(d[9]), "+f"(d[10]), "+f"(d[11]), "+f"(d[12]), "+f"(d[13]), "+f"(d[14]), "+f"(d[15]), "+f"(d[16]), "+f"(d[17]), "+f"(d[18]), "+f"(d[19]), "+f"(d[20]), "+f"(d[21]), "+f"(d[22]), "+f"(d[23]), "+f"(d[24]), "+f"(d[25]), "+f"(d[26]), "+f"(d[27]), "+f"(d[28]), "+f"(d[29]), "+f"(d[30]), "+f"(d[31])
        : "r"(a0), "r"(a1), "r"(a2), "r"(a3), "r"(blo), "r"(ob), "r"(hb), "r"(scale_d), "n"(TB));
}

template <int TB> __device__ __forceinline__ void wgmma_rs_n32(float (&d)[16], uint32_t a0, uint32_t a1, uint32_t a2, uint32_t a3, uint32_t blo, int ob, uint32_t hb, int scale_d) {
    asm volatile("{\n.reg .pred p;\n.reg .b32 tb;\n.reg .b64 db;\nsetp.ne.b32 p, %23, 0;\n"
        "add.u32 tb, %20, %21;\nmov.b64 db, {tb, %22};\n"
        "wgmma.mma_async.sync.aligned.m64n32k16.f32.bf16.bf16 {%0, %1, %2, %3, %4, %5, %6, %7, %8, %9, %10, %11, %12, %13, %14, %15}, {%16, %17, %18, %19}, db, p, 1, 1, %24;\n}\n"
        : "+f"(d[0]), "+f"(d[1]), "+f"(d[2]), "+f"(d[3]), "+f"(d[4]), "+f"(d[5]), "+f"(d[6]), "+f"(d[7]), "+f"(d[8]), "+f"(d[9]), "+f"(d[10]), "+f"(d[11]), "+f"(d[12]), "+f"(d[13]), "+f"(d[14]), "+f"(d[15])
        : "r"(a0), "r"(a1), "r"(a2), "r"(a3), "r"(blo), "r"(ob), "r"(hb), "r"(scale_d), "n"(TB));
}

template <int TB> __device__ __forceinline__ void wgmma_rsz_n64(float (&d)[32], uint32_t a0, uint32_t a1, uint32_t a2, uint32_t a3, uint32_t blo, int ob, uint32_t hb) {
    asm volatile("{\n.reg .pred p;\n.reg .b32 tb;\n.reg .b64 db;\nsetp.ne.b32 p, 0, 0;\n"
        "add.u32 tb, %36, %37;\nmov.b64 db, {tb, %38};\n"
        "wgmma.mma_async.sync.aligned.m64n64k16.f32.bf16.bf16 {%0, %1, %2, %3, %4, %5, %6, %7, %8, %9, %10, %11, %12, %13, %14, %15, %16, %17, %18, %19, %20, %21, %22, %23, %24, %25, %26, %27, %28, %29, %30, %31}, {%32, %33, %34, %35}, db, p, 1, 1, %39;\n}\n"
        : "=f"(d[0]), "=f"(d[1]), "=f"(d[2]), "=f"(d[3]), "=f"(d[4]), "=f"(d[5]), "=f"(d[6]), "=f"(d[7]), "=f"(d[8]), "=f"(d[9]), "=f"(d[10]), "=f"(d[11]), "=f"(d[12]), "=f"(d[13]), "=f"(d[14]), "=f"(d[15]), "=f"(d[16]), "=f"(d[17]), "=f"(d[18]), "=f"(d[19]), "=f"(d[20]), "=f"(d[21]), "=f"(d[22]), "=f"(d[23]), "=f"(d[24]), "=f"(d[25]), "=f"(d[26]), "=f"(d[27]), "=f"(d[28]), "=f"(d[29]), "=f"(d[30]), "=f"(d[31])
        : "r"(a0), "r"(a1), "r"(a2), "r"(a3), "r"(blo), "r"(ob), "r"(hb), "n"(TB));
}

template <int TB> __device__ __forceinline__ void wgmma_rsz_n32(float (&d)[16], uint32_t a0, uint32_t a1, uint32_t a2, uint32_t a3, uint32_t blo, int ob, uint32_t hb) {
    asm volatile("{\n.reg .pred p;\n.reg .b32 tb;\n.reg .b64 db;\nsetp.ne.b32 p, 0, 0;\n"
        "add.u32 tb, %20, %21;\nmov.b64 db, {tb, %22};\n"
        "wgmma.mma_async.sync.aligned.m64n32k16.f32.bf16.bf16 {%0, %1, %2, %3, %4, %5, %6, %7, %8, %9, %10, %11, %12, %13, %14, %15}, {%16, %17, %18, %19}, db, p, 1, 1, %23;\n}\n"
        : "=f"(d[0]), "=f"(d[1]), "=f"(d[2]), "=f"(d[3]), "=f"(d[4]), "=f"(d[5]), "=f"(d[6]), "=f"(d[7]), "=f"(d[8]), "=f"(d[9]), "=f"(d[10]), "=f"(d[11]), "=f"(d[12]), "=f"(d[13]), "=f"(d[14]), "=f"(d[15])
        : "r"(a0), "r"(a1), "r"(a2), "r"(a3), "r"(blo), "r"(ob), "r"(hb), "n"(TB));
}

constexpr int DM = 448;
constexpr int NTHREADS = 640;
constexpr uint32_t WAIT_LIMIT = 40000000u;

constexpr int SM_XN = 0;
constexpr int SM_WR = 114688;
constexpr int WR_STAGES = 5;
constexpr int SM_KV = SM_WR + WR_STAGES * 16384;
constexpr int KV_STAGES = 4;
constexpr int SM_BAR = SM_KV + KV_STAGES * 8192;
constexpr int SM_TOTAL = SM_BAR + 640;
constexpr int S2_STAGES = 5;
constexpr int QSTART = 5;
constexpr uint32_t XALIGN = 256;
constexpr int EPI2 = 2;
constexpr int POLLNS = 50;
constexpr int ROT = 512;
constexpr uint32_t TICK_F = 704;

constexpr int B_WFULL = 0, B_WEMPTY = 40, B_KVFULL = 80, B_KVEMPTY = 112, B_SFULL = 144, B_SEMPTY = 184;
constexpr int B_FLG = 224;
constexpr int B_XBFREE = 256, B_XBFULL = 264, B_EPOCH = 272, B_ASG = 280, B_OWNKV = 288, B_EPOCHVAL = 296, B_ASGVAL = 300, B_XLD = 304;
constexpr int B_XRD = 432;
constexpr int B_WOFULL = 448, B_WOFREE = 504;
constexpr int B_XT = 544;

__device__ __align__(1024) unsigned char g_KV[16 * 32 * 8192];
__device__ __align__(1024) unsigned char g_H[16 * 28 * 16384];
__device__ __align__(1024) unsigned char g_O[16 * 7 * 16384];
__device__ unsigned int g_flagKV[128 * 8];
__device__ unsigned int g_flagH[128 * 8];
__device__ unsigned int g_flagO[128 * 8];
__device__ unsigned int g_ticket;
__device__ unsigned long long g_key[64];
#define TS(i) do { } while (0)
#define TR(i) do { } while (0)
#define TRC(c, i) do { } while (0)
constexpr int SM_DBG = 0;

__device__ __forceinline__ uint32_t smem_u32(const void* p) { return (uint32_t)__cvta_generic_to_shared(p); }
__device__ __forceinline__ void mbar_init(uint32_t bar, int cnt) {
    asm volatile("mbarrier.init.shared::cta.b64 [%0], %1;" ::"r"(bar), "r"(cnt) : "memory");
}
__device__ __forceinline__ void mbar_expect_tx(uint32_t bar, uint32_t bytes) {
    asm volatile("mbarrier.arrive.expect_tx.shared::cta.b64 _, [%0], %1;" ::"r"(bar), "r"(bytes) : "memory");
}
__device__ __forceinline__ void mbar_arrive(uint32_t bar) {
    asm volatile("mbarrier.arrive.shared::cta.b64 _, [%0];" ::"r"(bar) : "memory");
}
__device__ __forceinline__ uint32_t mapa(uint32_t addr, uint32_t cta) {
    uint32_t r;
    asm volatile("mapa.shared::cluster.u32 %0, %1, %2;" : "=r"(r) : "r"(addr), "r"(cta));
    return r;
}
__device__ __forceinline__ void mbar_arrive_cluster(uint32_t remote_bar) {
    asm volatile("mbarrier.arrive.shared::cluster.b64 _, [%0];" ::"r"(remote_bar) : "memory");
}
__device__ __forceinline__ bool mbar_test(uint32_t bar, uint32_t parity) {
    uint32_t ok;
    asm volatile(
        "{\n.reg .pred p;\nmbarrier.test_wait.parity.shared::cta.b64 p, [%1], %2;\nselp.u32 %0, 1, 0, p;\n}"
        : "=r"(ok)
        : "r"(bar), "r"(parity)
        : "memory");
    return ok != 0;
}
__device__ __forceinline__ void mbar_wait(uint32_t bar, uint32_t parity) {
    asm volatile(
        "{\n.reg .pred p;\n.reg .b32 n;\n"
        "mbarrier.try_wait.parity.shared::cta.b64 p, [%0], %1, 10000;\n"
        "@p bra.uni DONE_%=;\n"
        "mov.u32 n, 4096;\n"
        "LOOP_%=:\n"
        "mbarrier.try_wait.parity.shared::cta.b64 p, [%0], %1, 10000;\n"
        "@p bra.uni DONE_%=;\n"
        "sub.u32 n, n, 1;\n"
        "setp.ne.u32 p, n, 0;\n"
        "@p bra.uni LOOP_%=;\n"
        "DONE_%=:\n}"
        ::"r"(bar), "r"(parity)
        : "memory");
}
__device__ __forceinline__ void mbar_wait_cluster(uint32_t bar, uint32_t parity) {
    asm volatile(
        "{\n.reg .pred p;\n.reg .b32 n;\n"
        "mov.u32 n, 4096;\n"
        "LOOP_%=:\n"
        "mbarrier.try_wait.parity.acquire.cluster.shared::cta.b64 p, [%0], %1, 10000;\n"
        "@p bra.uni DONE_%=;\n"
        "sub.u32 n, n, 1;\n"
        "setp.ne.u32 p, n, 0;\n"
        "@p bra.uni LOOP_%=;\n"
        "DONE_%=:\n}"
        ::"r"(bar), "r"(parity)
        : "memory");
}
__device__ __forceinline__ void flag_wait(const unsigned int* p, unsigned int target) {
    const uint32_t t0 = (uint32_t)clock();
    while (true) {
        unsigned int v;
        asm volatile("ld.acquire.gpu.global.u32 %0, [%1];" : "=r"(v) : "l"(p) : "memory");
        if ((int)(v - target) >= 0) break;
        if ((uint32_t)clock() - t0 > WAIT_LIMIT) break;
        __nanosleep(64);
    }
}
__device__ __forceinline__ void flag_set(unsigned int* p, unsigned int v) {
    asm volatile("fence.proxy.async.global;\nfence.acq_rel.gpu;\nst.relaxed.gpu.global.u32 [%0], %1;" ::"l"(p), "r"(v) : "memory");
}
__device__ __forceinline__ void fence_proxy_async_smem() { asm volatile("fence.proxy.async.shared::cta;" ::: "memory"); }
__device__ __forceinline__ void bar_sync(int id, int n) { asm volatile("bar.sync %0, %1;" ::"r"(id), "r"(n) : "memory"); }
__device__ __forceinline__ void bar_arrive(int id, int n) { asm volatile("bar.arrive %0, %1;" ::"r"(id), "r"(n) : "memory"); }

__device__ __forceinline__ void bulk_g2s(uint32_t dst, const void* src, uint32_t bytes, uint32_t bar) {
    asm volatile("cp.async.bulk.shared::cluster.global.mbarrier::complete_tx::bytes [%0], [%1], %2, [%3];" ::"r"(dst),
                 "l"(src), "r"(bytes), "r"(bar)
                 : "memory");
}
__device__ __forceinline__ void bulk_g2s_mc(uint32_t dst, const void* src, uint32_t bytes, uint32_t bar) {
    asm volatile("cp.async.bulk.shared::cluster.global.mbarrier::complete_tx::bytes.multicast::cluster [%0], [%1], %2, [%3], %4;" ::"r"(dst),
                 "l"(src), "r"(bytes), "r"(bar), "h"((uint16_t)3)
                 : "memory");
}
__device__ __forceinline__ void tma2d(uint32_t dst, const CUtensorMap* m, uint32_t bar, int c0, int c1) {
    asm volatile(
        "cp.async.bulk.tensor.2d.shared::cluster.global.mbarrier::complete_tx::bytes [%0], [%1, {%3, %4}], [%2];" ::"r"(dst),
        "l"(m), "r"(bar), "r"(c0), "r"(c1)
        : "memory");
}
__device__ __forceinline__ void tma3d_mc(uint32_t dst, const CUtensorMap* m, uint32_t bar, int c0, int c1, int c2) {
    asm volatile(
        "cp.async.bulk.tensor.3d.shared::cluster.global.mbarrier::complete_tx::bytes.multicast::cluster [%0], [%1, {%3, %4, %5}], [%2], %6;" ::"r"(dst),
        "l"(m), "r"(bar), "r"(c0), "r"(c1), "r"(c2), "h"((uint16_t)3)
        : "memory");
}
__device__ __forceinline__ void tma5d(uint32_t dst, const CUtensorMap* m, uint32_t bar, int c0, int c1, int c2, int c3, int c4) {
    asm volatile(
        "cp.async.bulk.tensor.5d.shared::cluster.global.mbarrier::complete_tx::bytes [%0], [%1, {%3, %4, %5, %6, %7}], [%2];" ::"r"(dst),
        "l"(m), "r"(bar), "r"(c0), "r"(c1), "r"(c2), "r"(c3), "r"(c4)
        : "memory");
}
__device__ __forceinline__ void l2_prefetch(const void* p, uint32_t bytes) {
    asm volatile("cp.async.bulk.prefetch.L2.global [%0], %1;" ::"l"(p), "r"(bytes) : "memory");
}
__device__ __forceinline__ void prefetch_tmap(const CUtensorMap* m) {
    asm volatile("prefetch.tensormap [%0];" ::"l"(m) : "memory");
}

__device__ __forceinline__ uint32_t desc_lo(uint32_t addr, uint32_t lbo) { return ((addr & 0x3FFFF) >> 4) | ((lbo >> 4) << 16); }
constexpr uint32_t HI_128 = (1024 >> 4) | (1u << 30);
constexpr uint32_t HI_64 = (512 >> 4) | (2u << 30);
__device__ __forceinline__ void wg_fence() { asm volatile("wgmma.fence.sync.aligned;" ::: "memory"); }
__device__ __forceinline__ void wg_commit() { asm volatile("wgmma.commit_group.sync.aligned;" ::: "memory"); }
template <int N>
__device__ __forceinline__ void wg_wait() { asm volatile("wgmma.wait_group.sync.aligned %0;" ::"n"(N) : "memory"); }
template <int N>
__device__ __forceinline__ void fence_regs(float (&d)[N]) {
#pragma unroll
    for (int i = 0; i < N; i++) asm volatile("" : "+f"(d[i])::"memory");
}

template <int N>
__device__ __forceinline__ void fence_regs_u(uint32_t (&d)[N]) {
#pragma unroll
    for (int i = 0; i < N; i++) asm volatile("" : "+r"(d[i])::"memory");
}

__device__ __forceinline__ uint32_t pack_bf16(float lo, float hi) {
    uint32_t r;
    asm("cvt.rn.bf16x2.f32 %0, %1, %2;" : "=r"(r) : "f"(hi), "f"(lo));
    return r;
}
__device__ __forceinline__ float bf_lo(uint32_t w) { return __uint_as_float(w << 16); }
__device__ __forceinline__ float bf_hi(uint32_t w) { return __uint_as_float(w & 0xffff0000u); }
__device__ __forceinline__ float bf_round(float x) { return bf_lo(pack_bf16(x, 0.f)); }
__device__ __forceinline__ uint32_t hsub2_bf(uint32_t a, uint32_t b) {
    uint32_t r;
    asm("sub.rn.bf16x2 %0, %1, %2;" : "=r"(r) : "r"(a), "r"(b));
    return r;
}
__device__ __forceinline__ uint32_t hmul2_bf(uint32_t a, uint32_t b) {
    uint32_t r;
    asm("mul.rn.bf16x2 %0, %1, %2;" : "=r"(r) : "r"(a), "r"(b));
    return r;
}
__device__ __forceinline__ uint32_t hfma2_bf(uint32_t a, uint32_t b, uint32_t c) {
    uint32_t r;
    asm("fma.rn.bf16x2 %0, %1, %2, %3;" : "=r"(r) : "r"(a), "r"(b), "r"(c));
    return r;
}
__device__ __forceinline__ uint32_t hmax2_bf(uint32_t a, uint32_t b) {
    uint32_t r;
    asm("max.bf16x2 %0, %1, %2;" : "=r"(r) : "r"(a), "r"(b));
    return r;
}
__device__ __forceinline__ float ex2(float x) {
    float r;
    asm("ex2.approx.ftz.f32 %0, %1;" : "=f"(r) : "f"(x));
    return r;
}
__device__ __forceinline__ float rcp_fast(float x) {
    float r;
    asm("rcp.approx.ftz.f32 %0, %1;" : "=f"(r) : "f"(x));
    return r;
}
__device__ __forceinline__ float silu_f(float g) {
    const float h = 0.5f * g;
    float t;
    asm("tanh.approx.f32 %0, %1;" : "=f"(t) : "f"(h));
    return fmaf(h, t, h);
}
__device__ __forceinline__ uint32_t hadd2_bf(uint32_t a, uint32_t b) {
    uint32_t r;
    asm("add.rn.bf16x2 %0, %1, %2;" : "=r"(r) : "r"(a), "r"(b));
    return r;
}
__device__ __forceinline__ void stg128(void* p, uint32_t a, uint32_t b, uint32_t c, uint32_t d) {
    asm volatile("st.global.v4.b32 [%0], {%1, %2, %3, %4};" ::"l"(p), "r"(a), "r"(b), "r"(c), "r"(d) : "memory");
}
__device__ __forceinline__ void stg64(void* p, uint32_t a, uint32_t b) {
    asm volatile("st.global.v2.b32 [%0], {%1, %2};" ::"l"(p), "r"(a), "r"(b) : "memory");
}

__device__ __forceinline__ void mma_stats(float (&c)[4], uint32_t a, uint32_t b) {
    asm volatile(
        "mma.sync.aligned.m16n8k16.row.col.f32.bf16.bf16.f32 {%0, %1, %2, %3}, {%4, %6, %5, %6}, {%4, %5}, {%0, %1, %2, %3};"
        : "+f"(c[0]), "+f"(c[1]), "+f"(c[2]), "+f"(c[3])
        : "r"(a), "r"(b), "r"(0x3f803f80u));
}
__device__ __forceinline__ uint32_t ln_norm(uint32_t x, uint32_t mb2, uint32_t rh2, uint32_t rl2) {
    const uint32_t d = hsub2_bf(x, mb2);
    return hfma2_bf(d, rh2, hmul2_bf(d, rl2));
}
__device__ __forceinline__ void ln_process(uint4 (&v)[14], uint32_t xn_base, int lane, uint32_t rdbar) {
    float c0[4] = {0.f, 0.f, 0.f, 0.f}, c1[4] = {0.f, 0.f, 0.f, 0.f}, c2[4] = {0.f, 0.f, 0.f, 0.f}, c3[4] = {0.f, 0.f, 0.f, 0.f};
#pragma unroll
    for (int i = 0; i < 14; i += 2) {
        mma_stats(c0, v[i].x, v[i].y);
        mma_stats(c1, v[i].z, v[i].w);
        mma_stats(c2, v[i + 1].x, v[i + 1].y);
        mma_stats(c3, v[i + 1].z, v[i + 1].w);
    }
    __syncwarp();
    if (lane == 0) mbar_arrive(rdbar);
    const int gq = lane >> 2, q = lane & 3;
    const bool odd = gq & 1;
    float ss = odd ? (c0[1] + c1[1]) + (c2[1] + c3[1]) : (c0[0] + c1[0]) + (c2[0] + c3[0]);
    float sm = odd ? (c0[3] + c1[3]) + (c2[3] + c3[3]) : (c0[2] + c1[2]) + (c2[2] + c3[2]);
    const int srcl = gq * 4 + (gq >> 1);
    ss = __shfl_sync(0xffffffffu, ss, srcl);
    sm = __shfl_sync(0xffffffffu, sm, srcl);
    float mean = sm * (1.0f / DM);
    mean = fmaf(fmaf(-(float)DM, mean, sm), 1.0f / DM, mean);
    float var = fmaf(-mean, mean, ss * (1.0f / DM));
    if (__any_sync(0xffffffffu, !(mean * mean <= 32.0f * var))) {
        float a0 = 0.f, a1 = 0.f;
#pragma unroll
        for (int i = 0; i < 14; i++) {
            float t;
            t = bf_lo(v[i].x) - mean; a0 = fmaf(t, t, a0);
            t = bf_hi(v[i].x) - mean; a1 = fmaf(t, t, a1);
            t = bf_lo(v[i].y) - mean; a0 = fmaf(t, t, a0);
            t = bf_hi(v[i].y) - mean; a1 = fmaf(t, t, a1);
            t = bf_lo(v[i].z) - mean; a0 = fmaf(t, t, a0);
            t = bf_hi(v[i].z) - mean; a1 = fmaf(t, t, a1);
            t = bf_lo(v[i].w) - mean; a0 = fmaf(t, t, a0);
            t = bf_hi(v[i].w) - mean; a1 = fmaf(t, t, a1);
        }
        a0 += a1;
        a0 += __shfl_xor_sync(0xffffffffu, a0, 1);
        a0 += __shfl_xor_sync(0xffffffffu, a0, 2);
        var = a0 * (1.0f / DM);
    }
    asm volatile("" : "+f"(var));
    TRC(threadIdx.x == (NTHREADS - ROT) % NTHREADS, 256 + 56);
    float sq;
    asm("sqrt.approx.f32 %0, %1;" : "=f"(sq) : "f"(bf_round(bf_round(var) + 1e-5f)));
    const float r = rcp_fast(bf_round(sq));
    const float rh = bf_round(r);
    const float rl = (r - rh) * 0.99951171875f;
    const uint32_t rh2 = pack_bf16(rh, rh);
    const uint32_t rl2 = pack_bf16(rl, rl);
    const uint32_t mb2 = pack_bf16(mean, mean);
    const uint32_t dst0 = xn_base + gq * 128 + (((q + (odd ? 4 : 0)) ^ gq) << 4);
    const uint32_t dst1 = xn_base + gq * 128 + (((q + (odd ? 0 : 4)) ^ gq) << 4);
#pragma unroll
    for (int i = 0; i < 14; i++) {
        v[i].x = ln_norm(v[i].x, mb2, rh2, rl2);
        v[i].y = ln_norm(v[i].y, mb2, rh2, rl2);
        v[i].z = ln_norm(v[i].z, mb2, rh2, rl2);
        v[i].w = ln_norm(v[i].w, mb2, rh2, rl2);
        asm volatile("" : "+r"(v[i].x), "+r"(v[i].y), "+r"(v[i].z), "+r"(v[i].w));
    }
    TRC(threadIdx.x == (NTHREADS - ROT) % NTHREADS, 256 + 57);
    mbar_wait(rdbar, 0);
    TRC(threadIdx.x == (NTHREADS - ROT) % NTHREADS && v[0].x != 0x12345, 256 + 58);
#pragma unroll
    for (int i = 0; i < 14; i++) {
        asm volatile("st.shared.v4.b32 [%0], {%1, %2, %3, %4};" ::"r"(((i & 1) ? dst1 : dst0) + (i >> 1) * 8192),
                     "r"(v[i].x), "r"(v[i].y), "r"(v[i].z), "r"(v[i].w)
                     : "memory");
    }
}

struct Params {
    const __nv_bfloat16* x;
    const __nv_bfloat16* wqkv;
    const __nv_bfloat16* w1;
    const __nv_bfloat16* w3;
    const __nv_bfloat16* w2;
    const __nv_bfloat16* wo;
    __nv_bfloat16* out;
    int swap13;
};

struct WState {
    uint32_t slot, ph, it;
};
template <bool MIX, bool FIRST>
__device__ __forceinline__ void w_issue(float (&acc)[64], const WState& ws, uint32_t ad, uint32_t blo, uint32_t mlo) {
    const uint32_t bd = blo + ws.slot * 1024, md = mlo + ws.slot * 1024;
    wg_fence();
#pragma unroll
    for (int k = 0; k < 4; k++) {
        const int bo = (k >> 1) * 512;
        if constexpr (MIX) {
            if (FIRST && k == 0) wgmma_ssz_n64<1>(*reinterpret_cast<float(*)[32]>(&acc[0]), ad, k * 2, HI_128, md, bo + (k & 1) * 64, HI_64);
            else wgmma_ss_n64<1>(*reinterpret_cast<float(*)[32]>(&acc[0]), ad, k * 2, HI_128, md, bo + (k & 1) * 64, HI_64, 1);
        } else {
            if (FIRST && k == 0) wgmma_ssz_n128<1>(acc, ad, k * 2, HI_128, bd, bo + (k & 1) * 128, HI_128);
            else wgmma_ss_n128<1>(acc, ad, k * 2, HI_128, bd, bo + (k & 1) * 128, HI_128, 1);
        }
    }
    wg_commit();
    TRC(threadIdx.x == (NTHREADS - ROT) % NTHREADS, ws.it);
}
__device__ __forceinline__ void w_release_prev(const WState& ws, uint32_t sb, uint32_t peer_sb, bool elect) {
    if (elect && ws.it > 0) {
        const uint32_t ps = ws.slot >= 1 ? ws.slot - 1 : WR_STAGES - 1;
        if (ws.it - 1 < 35 - WR_STAGES) {
            mbar_arrive(sb + SM_BAR + B_WEMPTY + ps * 8);
            mbar_arrive_cluster(peer_sb + SM_BAR + B_WEMPTY + ps * 8);
        } else {
            mbar_arrive(sb + SM_BAR + B_SEMPTY + ps * 8);
        }
    }
}
__device__ __forceinline__ void w_next(WState& ws, uint32_t sb) {
    ws.it++;
    if (++ws.slot == WR_STAGES) { ws.slot = 0; ws.ph ^= 1; }
    TRC(threadIdx.x == (NTHREADS - ROT) % NTHREADS, 128 + ws.it);
    mbar_wait(ws.it < 35 ? sb + SM_BAR + B_WFULL + ws.slot * 8 : sb + SM_BAR + B_SFULL, ws.it < 35 ? ws.ph : 0);
    wg_wait<0>();
}
template <bool MIX, int NU, class EPI>
__device__ __forceinline__ void gemm1_chunk(uint32_t (&pk)[32], WState& ws, uint32_t sb, uint32_t alo, uint32_t blo, uint32_t mlo,
                                            bool elect, uint32_t peer_sb, EPI&& epi) {
    float acc[64];
    w_issue<MIX, true>(acc, ws, alo, blo, mlo);
    w_release_prev(ws, sb, peer_sb, elect);
    epi(0);
    w_next(ws, sb);
#pragma unroll
    for (int s = 1; s < NU; s++) {
        w_issue<MIX, false>(acc, ws, alo + s * 512, blo, mlo);
        w_release_prev(ws, sb, peer_sb, elect);
        epi(s);
        w_next(ws, sb);
    }
#pragma unroll 1
    for (int s = NU; s < 7; s++) {
        w_issue<MIX, false>(acc, ws, alo + s * 512, blo, mlo);
        w_release_prev(ws, sb, peer_sb, elect);
        if (!MIX && s == QSTART) epi(s);
        w_next(ws, sb);
    }
    if constexpr (MIX) {
        fence_regs(*reinterpret_cast<float(*)[32]>(&acc[0]));
#pragma unroll
        for (int i = 0; i < 8; i++) {
            pk[8 + i] = pack_bf16(acc[2 * i], acc[2 * i + 1]);
            pk[24 + i] = pack_bf16(acc[16 + 2 * i], acc[16 + 2 * i + 1]);
        }
    } else {
        fence_regs(acc);
#pragma unroll
        for (int i = 0; i < 32; i++) pk[i] = pack_bf16(acc[2 * i], acc[2 * i + 1]);
    }
    fence_regs_u(pk);
    asm volatile("{\n.reg .pred p;\nsetp.gt.u32 p, %0, 0x7fffffff;\n@p exit;\n}" ::"r"(sb) : "memory");
}

__device__ __forceinline__ uint32_t hval2(uint32_t g2, uint32_t u2) {
    return hmul2_bf(pack_bf16(silu_f(bf_lo(g2)), silu_f(bf_hi(g2))), u2);
}

__device__ __forceinline__ void final_phase(float (&f)[56], size_t off0, uint32_t sb, uint32_t peer_sb,
                                            int tid, int w, const Params& P, int R, int rloc0, int q) {
    TRC(tid == 0, 256 + 32);
    uint32_t snd[14];
#pragma unroll
    for (int i = 0; i < 14; i++) {
        snd[i] = pack_bf16(R ? f[2 * i] : f[28 + 2 * i], R ? f[2 * i + 1] : f[28 + 2 * i + 1]);
        f[2 * i] = R ? f[28 + 2 * i] : f[2 * i];
        f[2 * i + 1] = R ? f[28 + 2 * i + 1] : f[2 * i + 1];
    }
    mbar_wait(sb + SM_BAR + B_XBFREE, 0);
    TRC(tid == 0, 256 + 33);
    {
        const uint32_t rbar = peer_sb + SM_BAR + B_XBFULL;
        const uint32_t rdst = peer_sb + SM_KV + tid * 16;
#pragma unroll
        for (int i = 0; i < 3; i++) {
            asm volatile("st.async.shared::cluster.mbarrier::complete_tx::bytes.v4.b32 [%0], {%1, %2, %3, %4}, [%5];" ::"r"(
                             rdst + i * 4096),
                         "r"(snd[4 * i]), "r"(snd[4 * i + 1]), "r"(snd[4 * i + 2]), "r"(snd[4 * i + 3]), "r"(rbar)
                         : "memory");
        }
        asm volatile("st.async.shared::cluster.mbarrier::complete_tx::bytes.v2.b32 [%0], {%1, %2}, [%3];" ::"r"(
                         peer_sb + SM_KV + 3 * 4096 + tid * 8),
                     "r"(snd[12]), "r"(snd[13]), "r"(rbar)
                     : "memory");
    }
    TRC(tid == 0, 256 + 34);
    float sacc[28];
#pragma unroll
    for (int i = 0; i < 28; i++) sacc[i] = 0.f;
    fence_regs(sacc);
    uint32_t gg[14], xr[14];
#pragma unroll
    for (int i = 0; i < 14; i++) gg[i] = xr[i] = 0;
    bool gdone = false;
#pragma unroll 1
    for (uint32_t k = 0; k < 8; k++) {
        if (!gdone && (k == 7 || !mbar_test(sb + SM_BAR + B_WOFULL + k * 8, 0))) {
            gdone = true;
            mbar_wait_cluster(sb + SM_BAR + B_XBFULL, 0);
            TRC(tid == 0, 256 + 37);
#pragma unroll
            for (int i = 0; i < 3; i++) {
                asm volatile("ld.shared.v4.b32 {%0, %1, %2, %3}, [%4];"
                             : "=r"(gg[4 * i]), "=r"(gg[4 * i + 1]), "=r"(gg[4 * i + 2]), "=r"(gg[4 * i + 3])
                             : "r"(sb + SM_KV + tid * 16 + i * 4096));
            }
            asm volatile("ld.shared.v2.b32 {%0, %1}, [%2];" : "=r"(gg[12]), "=r"(gg[13]) : "r"(sb + SM_KV + 3 * 4096 + tid * 8));
#pragma unroll
            for (int i = 0; i < 14; i++) {
                const uint32_t f2 = pack_bf16(f[2 * i] + bf_lo(gg[i]), f[2 * i + 1] + bf_hi(gg[i]));
                gg[i] = pack_bf16(silu_f(bf_lo(f2)), silu_f(bf_hi(f2)));
            }
            fence_regs_u(gg);
            mbar_wait(sb + SM_BAR + B_XT, 0);
#pragma unroll
            for (int i = 0; i < 7; i++) {
                const uint32_t a = sb + SM_KV + 16384 + rloc0 * 128 + (((i + R) ^ (rloc0 & 7)) << 4) + q * 4;
                asm volatile("ld.shared.b32 %0, [%1];" : "=r"(xr[2 * i]) : "r"(a));
                asm volatile("ld.shared.b32 %0, [%1];" : "=r"(xr[2 * i + 1]) : "r"(a + 1024));
            }
            TRC(tid == 0, 256 + 38);

        }
        if (k == 7) break;
        const uint32_t sl = (k < 2 ? k + 4 : k + 2) % S2_STAGES;
        const uint32_t ad = desc_lo(k < 2 ? sb + SM_XN + w * 57344 + k * 8192 : sb + SM_WR + sl * 16384 + w * 8192, 16);
        const uint32_t bd = desc_lo(sb + SM_XN + (k < 2 ? 57344 : 0) + (sl + 2) * 8192, 8192) + R;
        mbar_wait(sb + SM_BAR + B_WOFULL + k * 8, 0);
        TRC(tid == 0, 35 + 14 + k);
        wg_fence();
#pragma unroll
        for (int kk = 0; kk < 4; kk++) wgmma_ss_n56<1>(sacc, ad, kk * 2, HI_128, bd, kk * 128, HI_128, 1);
        wg_commit();
    }
    wg_wait<0>();
    fence_regs(sacc);
#pragma unroll
    for (int i = 0; i < 7; i++) {
        const uint32_t p01 = hmul2_bf(pack_bf16(sacc[4 * i], sacc[4 * i + 1]), gg[2 * i]);
        const uint32_t p23 = hmul2_bf(pack_bf16(sacc[4 * i + 2], sacc[4 * i + 3]), gg[2 * i + 1]);
        *reinterpret_cast<uint32_t*>(P.out + off0 + 8 * i) = hadd2_bf(xr[2 * i], p01);
        *reinterpret_cast<uint32_t*>(P.out + off0 + 8 * DM + 8 * i) = hadd2_bf(xr[2 * i + 1], p23);
    }
    asm volatile("barrier.cluster.arrive.relaxed.aligned;" ::: "memory");
}

__device__ __forceinline__ void kv_wait(uint32_t sb, uint32_t st) {
    mbar_wait(sb + SM_BAR + B_KVFULL + (st % KV_STAGES) * 8, (st / KV_STAGES) & 1);
}
__device__ __forceinline__ void issue_s(float (&s)[32], const uint32_t (&qf)[8], uint32_t kd) {
    wgmma_rsz_n64<0>(s, qf[0], qf[1], qf[2], qf[3], kd, 0, HI_64);
    wgmma_rs_n64<0>(s, qf[4], qf[5], qf[6], qf[7], kd, 2, HI_64, 1);
}
__device__ __forceinline__ void scale_scores(const float (&s)[32], uint32_t (&tt)[16]) {
    const uint32_t SC_HI = 0x3e423e42u, SC_LO = 0xb9f7b9f7u;
#pragma unroll
    for (int i = 0; i < 16; i++) {
        const uint32_t a = pack_bf16(s[2 * i], s[2 * i + 1]);
        tt[i] = hfma2_bf(a, SC_HI, hmul2_bf(a, SC_LO));
    }
}
template <bool LOWER>
__device__ __forceinline__ void mask_scores(uint32_t (&tt)[16], uint32_t diag2) {
#pragma unroll
    for (int c = -8; c < 64; c += 8) {
        const uint32_t c2 = (__float_as_uint((float)c) >> 16) | (__float_as_uint((float)(c + 1)) & 0xffff0000u);
        uint32_t keep;
        if (LOWER) asm("set.le.u32.bf16x2 %0, %1, %2;" : "=r"(keep) : "r"(c2), "r"(diag2));
        else asm("set.gt.u32.bf16x2 %0, %1, %2;" : "=r"(keep) : "r"(c2), "r"(diag2));
        if (c >= 0) asm("lop3.b32 %0, %1, %0, %2, 0xCA;" : "+r"(tt[2 * (c / 8)]) : "r"(keep), "r"(0xff80ff80u));
        if (c < 56) asm("lop3.b32 %0, %1, %0, %2, 0xCA;" : "+r"(tt[2 * (c / 8 + 1) + 1]) : "r"(keep), "r"(0xff80ff80u));
    }
}
__device__ __forceinline__ uint32_t row_max(const uint32_t (&tt)[16]) {
    uint32_t mx0 = tt[0], mx1 = tt[1];
#pragma unroll
    for (int i = 1; i < 8; i++) {
        mx0 = hmax2_bf(mx0, tt[2 * i]);
        mx1 = hmax2_bf(mx1, tt[2 * i + 1]);
    }
    uint32_t mm = hmax2_bf(__byte_perm(mx0, mx1, 0x5410), __byte_perm(mx0, mx1, 0x7632));
    mm = hmax2_bf(mm, __shfl_xor_sync(0xffffffffu, mm, 1));
    mm = hmax2_bf(mm, __shfl_xor_sync(0xffffffffu, mm, 2));
    return mm;
}
__device__ __forceinline__ void exp_scores(uint32_t (&tt)[16], uint32_t mm) {
    const uint32_t m0 = __byte_perm(mm, mm, 0x1010), m1 = __byte_perm(mm, mm, 0x3232);
#pragma unroll
    for (int i = 0; i < 16; i++) {
        const uint32_t d = hsub2_bf(tt[i], (i & 1) ? m1 : m0);
        const uint32_t a = hfma2_bf(d, 0x3ee33ee3u, d);
        asm("ex2.approx.ftz.bf16x2 %0, %1;" : "=r"(tt[i]) : "r"(a));
    }
}

__device__ __forceinline__ void attention_tile(const int T, uint32_t sb, int g, int j, int tid, int wq, int lane) {
    const bool elect = (tid & 127) == 0;
    const int q = lane & 3;
    const int rl = wq * 16 + (lane >> 2);
    const uint32_t kd0 = desc_lo(sb + SM_KV, 512);
    const uint32_t diag2 = pack_bf16((float)(rl - 2 * q), (float)(rl - 2 * q));
    uint32_t qf[8], qn[8];
    {
        float qa[32];
#pragma unroll
        for (int i = 0; i < 32; i++) qa[i] = 0.f;
        fence_regs(qa);
        const uint32_t alo = desc_lo(sb + SM_XN + T * 57344, 16);
        const uint32_t blo = desc_lo(sb + SM_KV, 8192) + (j & 1);
        bar_sync(8 + T, 256);
#pragma unroll 1
        for (uint32_t s = 0; s < 7; s++) {
            kv_wait(sb, s);
            wg_fence();
#pragma unroll
            for (int k = 0; k < 4; k++) wgmma_ss_n64<1>(qa, alo + s * 512, k * 2, HI_128, blo + (s % KV_STAGES) * 512, k * 128, HI_128, 1);
            wg_commit();
            wg_wait<1>();
            if (elect && s > 0) mbar_arrive(sb + SM_BAR + B_KVEMPTY + ((s - 1) % KV_STAGES) * 8);
        }
        wg_wait<0>();
        if (elect) mbar_arrive(sb + SM_BAR + B_KVEMPTY + (6 % KV_STAGES) * 8);
        fence_regs(qa);
        bar_arrive(13 + T, 256);
#pragma unroll
        for (int hh = 0; hh < 2; hh++) {
#pragma unroll
            for (int rh = 0; rh < 2; rh++) {
                uint32_t wv[4];
#pragma unroll
                for (int i = 0; i < 4; i++) wv[i] = pack_bf16(qa[4 * (3 * hh + i) + 2 * rh], qa[4 * (3 * hh + i) + 2 * rh + 1]);
                if (hh == 0 && q >= 2) wv[3] = 0u;
                if (hh == 1 && q < 2) wv[0] = 0u;
                const bool b0 = q & 1, b1 = q & 2;
                uint32_t x0 = __shfl_xor_sync(0xffffffffu, b0 ? wv[0] : wv[1], 1);
                uint32_t x1 = __shfl_xor_sync(0xffffffffu, b0 ? wv[2] : wv[3], 1);
                if (b0) { wv[0] = x0; wv[2] = x1; } else { wv[1] = x0; wv[3] = x1; }
                x0 = __shfl_xor_sync(0xffffffffu, b1 ? wv[0] : wv[2], 2);
                x1 = __shfl_xor_sync(0xffffffffu, b1 ? wv[1] : wv[3], 2);
                if (b1) { wv[0] = x0; wv[1] = x1; } else { wv[2] = x0; wv[3] = x1; }
#pragma unroll
                for (int c = 0; c < 4; c++) {
                    if (hh == 0) qf[(c >> 1) * 4 + (c & 1) * 2 + rh] = wv[c];
                    else qn[(c >> 1) * 4 + (c & 1) * 2 + rh] = wv[c];
                }
            }
        }
    }
    TRC(tid == 256, 256 + 30);
    float s[32];
    kv_wait(sb, 7);
    wg_fence();
    issue_s(s, qf, kd0 + (7 % KV_STAGES) * 512);
    wg_commit();
    wg_wait<0>();
#pragma unroll 1
    for (int hh = 0; hh < 2; hh++) {
        uint32_t st = 7 + 6 * hh;
        float o[16];
        uint32_t tt[16];
        uint32_t mm = 0xff80ff80u;
#pragma unroll
        for (int i = 0; i < 16; i++) o[i] = 0.f;
#pragma unroll
        for (int n = 0; n < 5; n++) {
            const uint32_t stn = n < 3 ? st + 1 : (n == 3 || hh == 1 ? 7 + 6 * hh + 5 - T : 13);
            const int rel = n < 4 ? 4 - n - T : 4 * T;
            fence_regs(s);
            scale_scores(s, tt);
            const bool none = 2 * g + T + rel < 4;
            if (rel == 4 || none) mask_scores<true>(tt, none ? 0xc2c8c2c8u : diag2);
            else if (rel == 0) mask_scores<false>(tt, diag2);
            const uint32_t mn = hmax2_bf(mm, row_max(tt));
            const float al0 = ex2((bf_lo(mm) - bf_lo(mn)) * 1.4426950408889634f);
            const float al1 = ex2((bf_hi(mm) - bf_hi(mn)) * 1.4426950408889634f);
            mm = mn;
#pragma unroll
            for (int i = 0; i < 4; i++) {
                o[4 * i] *= al0;
                o[4 * i + 1] *= al0;
                o[4 * i + 2] *= al1;
                o[4 * i + 3] *= al1;
            }
            exp_scores(tt, mm);
            if (n == 4) {
#pragma unroll
                for (int i = 0; i < 8; i++) qf[i] = qn[i];
            }
            fence_regs(o);
            fence_regs_u(tt);
            fence_regs_u(qf);
            TRC(tid == 256, 192 + hh * 10 + n * 2);
            kv_wait(sb, stn);
            wg_fence();
            issue_s(s, qf, kd0 + (stn % KV_STAGES) * 512);
            const uint32_t kd = kd0 + (st % KV_STAGES) * 512;
#pragma unroll
            for (int k = 0; k < 4; k++)
                wgmma_rs_n32<1>(o, tt[4 * k], tt[4 * k + 1], tt[4 * k + 2], tt[4 * k + 3], kd, 256 + k * 64, HI_64, 1);
            wg_commit();
            wg_wait<0>();
            fence_regs(o);
            TRC(tid == 256, 192 + hh * 10 + n * 2 + 1);
            if (elect) {
                mbar_arrive(sb + SM_BAR + B_KVEMPTY + (st % KV_STAGES) * 8);
                if (n == 4) mbar_arrive(sb + SM_BAR + B_KVEMPTY + (st % KV_STAGES) * 8);
            }
            st = stn;
        }
        const float la = hh == 0 ? o[8] : o[0];
        const float lb = hh == 0 ? o[10] : o[2];
        const int srcl = (lane & ~3) | (hh == 0 ? 3 : 0);
        const float i0 = rcp_fast(__shfl_sync(0xffffffffu, la, srcl));
        const float i1 = rcp_fast(__shfl_sync(0xffffffffu, lb, srcl));
        const int C = 7 * j + 3 * hh + q;
        const int kb = C >> 3, c = C & 7;
#pragma unroll
        for (int rh = 0; rh < 2; rh++) {
            const float inv = rh ? i1 : i0;
            const uint32_t w0 = pack_bf16(o[0 + 2 * rh] * inv, o[1 + 2 * rh] * inv);
            const uint32_t w1 = pack_bf16(o[4 + 2 * rh] * inv, o[5 + 2 * rh] * inv);
            const uint32_t w2 = pack_bf16(o[8 + 2 * rh] * inv, o[9 + 2 * rh] * inv);
            const uint32_t w3 = pack_bf16(o[12 + 2 * rh] * inv, o[13 + 2 * rh] * inv);
            const int rloc = T * 64 + rl + 8 * rh;
            unsigned char* dst = g_O + (size_t)(g * 7 + kb) * 16384 + rloc * 128 + ((c ^ (rloc & 7)) << 4);
            if (hh == 0 && q == 3) stg64(dst, w0, w1);
            else if (hh == 1 && q == 0) stg64(dst + 8, w2, w3);
            else stg128(dst, w0, w1, w2, w3);
        }
    }
}

template <bool SW>
__global__ void __cluster_dims__(2, 1, 1) __launch_bounds__(NTHREADS, 1)
fused_kernel(const __grid_constant__ CUtensorMap tm_qk, const __grid_constant__ CUtensorMap tm_v,
             const __grid_constant__ CUtensorMap tm_w13, const __grid_constant__ CUtensorMap tm_w13m,
             const __grid_constant__ CUtensorMap tm_w2, const __grid_constant__ CUtensorMap tm_w2b,
             const __grid_constant__ CUtensorMap tm_wo, const __grid_constant__ CUtensorMap tm_x, const Params P) {
    extern __shared__ __align__(1024) unsigned char smem[];
    const uint32_t sb = smem_u32(smem);
    const int tid = (threadIdx.x + ROT) % NTHREADS;
    const int warp = __shfl_sync(0xffffffffu, tid >> 5, 0), lane = tid & 31;
    const int wg = warp >> 2;
    const int rank = blockIdx.x & 1;
    const int cl = blockIdx.x >> 1;
    const int G = cl & 7, j = cl >> 3;
    const int g = 2 * G + rank;
    const uint32_t peer_sb = mapa(sb, rank ^ 1);
    const int fa = (j & 1) ? 224 * j + 32 : 224 * j;
    const int fm = (j & 1) ? 224 * j : 224 * j + 192;
    const int qcol = 56 * j - 8 * (j & 1);

    TRC(tid == 0, 256 + (0));

    if (wg == 4) {
        asm volatile("setmaxnreg.dec.sync.aligned.u32 32;");
        if (lane == 0) {
            if (warp == 16) {
#pragma unroll
                for (int i = 0; i < 5; i++) {
                    mbar_init(sb + SM_BAR + B_WFULL + i * 8, 1);
                    mbar_init(sb + SM_BAR + B_WEMPTY + i * 8, 4);
                }
            } else if (warp == 17) {
#pragma unroll
                for (int i = 0; i < 4; i++) {
                    mbar_init(sb + SM_BAR + B_KVFULL + i * 8, 1);
                    mbar_init(sb + SM_BAR + B_KVEMPTY + i * 8, 2);
                }
#pragma unroll
                for (int i = 0; i < 5; i++) mbar_init(sb + SM_BAR + B_XBFREE + i * 8, 1);
                mbar_expect_tx(sb + SM_BAR + B_XBFULL, 7 * 2048);
            } else if (warp == 18) {
#pragma unroll
                for (int i = 0; i < 5; i++) {
                    mbar_init(sb + SM_BAR + B_SFULL + i * 8, 1);
                    mbar_init(sb + SM_BAR + B_SEMPTY + i * 8, 2);
                }
#pragma unroll
                for (int i = 0; i < 4; i++) mbar_init(sb + SM_BAR + B_FLG + i * 8, 1);
                mbar_init(sb + SM_BAR + B_XT, 1);
            } else {
#pragma unroll
                for (int i = 0; i < 7; i++) {
                    mbar_init(sb + SM_BAR + B_WOFULL + i * 8, 1);
                    mbar_expect_tx(sb + SM_BAR + B_WOFULL + i * 8, 16384 + 8192);
                }
#pragma unroll
                for (int i = 0; i < 5; i++) mbar_init(sb + SM_BAR + B_WOFREE + i * 8, 4);
            }
            asm volatile("fence.mbarrier_init.release.cluster;" ::: "memory");
        }
        __syncwarp();
        const uint32_t key = (uint32_t)clock();
        asm volatile("barrier.cluster.arrive.relaxed.aligned;" ::: "memory");
        if (tid == 19 * 32) {
            l2_prefetch(reinterpret_cast<const char*>(P.wqkv) + (size_t)blockIdx.x * 9408, 9408);
        } else if (tid == 16 * 32) {
            prefetch_tmap(&tm_qk);
        } else if (tid == 17 * 32) {
            prefetch_tmap(&tm_v);
            prefetch_tmap(&tm_w13m);
            prefetch_tmap(&tm_w13);
            prefetch_tmap(&tm_w2);
            prefetch_tmap(&tm_w2b);
            prefetch_tmap(&tm_wo);
            prefetch_tmap(&tm_x);
        }
        __syncwarp();
        asm volatile("barrier.cluster.wait.aligned;" ::: "memory");
        TRC(tid == 512, 256 + 59);
        if (warp == 16) {
            const bool lead = lane == 0;
            {
                uint32_t slot = 0, ph = 1;
                auto acquire = [&](uint32_t bytes) -> uint32_t {
                    mbar_wait(sb + SM_BAR + B_WEMPTY + slot * 8, ph);
                    const uint32_t fb = sb + SM_BAR + B_WFULL + slot * 8;
                    if (lead) mbar_expect_tx(fb, bytes);
                    return fb;
                };
                auto advance = [&]() { if (++slot == WR_STAGES) { slot = 0; ph ^= 1; } };
                const uint32_t dst0 = sb + SM_WR + rank * 8192;
#pragma unroll 1
                for (int s = 0; s < 7; s++) {
                    if (s == 2) mbar_wait(sb + SM_BAR + B_XLD + 7 * 8, 0);
                    const uint32_t fb = acquire(16384);
                    if (lead) tma3d_mc(dst0 + slot * 16384, &tm_qk, fb, qcol, 64 * s + 32 * rank, 1);
                    TRC(lead, 64 + s);
                    advance();
                }
#pragma unroll 1
                for (int s = 0; s < 7; s++) {
                    const uint32_t fb = acquire(8192);
                    if (lead) tma3d_mc(dst0 + slot * 16384, &tm_w13m, fb, fm, 64 * s + 32 * rank, 0);
                    TRC(lead, 64 + 7 + s);
                    advance();
                }
                int col = fa, k0 = 32 * rank;
#pragma unroll 1
                for (int i = 0; i < 21; i++) {
                    const uint32_t fb = acquire(16384);
                    if (lead) tma3d_mc(dst0 + slot * 16384, &tm_w13, fb, col, k0, 0);
                    TRC(lead, 64 + 14 + i);
                    k0 += 64;
                    if (k0 >= 448) { k0 -= 448; col += 64; }
                    advance();
                }
            }
            {
                uint32_t asg;
                mbar_wait(sb + SM_BAR + B_ASG, 0);
                asm volatile("ld.shared.u32 %0, [%1];" : "=r"(asg) : "r"(sb + SM_BAR + B_ASGVAL));
                asg = __reduce_max_sync(0xffffffffu, asg);
                const int gt = asg >> 2, pcol = asg & 3;
                uint32_t slot = 0, ph = 0;
#pragma unroll 1
                for (int p = 0; p < 3; p++) {
                    const uint32_t cnt = p == 0 ? 6 : 4;
                    const uint32_t tab = p == 0 ? 0xB740A3u : (p == 1 ? 0xC851u : 0xD962u);
                    mbar_wait(sb + SM_BAR + B_FLG + p * 8, 0);
                    mbar_wait(sb + SM_BAR + B_SEMPTY + slot * 8, ph);
                    const uint32_t tick = (__reduce_max_sync(0xffffffffu, (uint32_t)clock()) + 160) / TICK_F + 1;
                    uint32_t target = tick * TICK_F;
                    uint32_t e = p == 0 ? tick % 6u : tick & 3u;
#pragma unroll 1
                    for (uint32_t i = 0; i < cnt; i++) {
                        const uint32_t fb = sb + SM_BAR + B_SFULL + slot * 8;
                        const uint32_t da = sb + SM_WR + slot * 16384;
                        const uint32_t db = sb + SM_XN + (slot + 2) * 8192;
                        const int kb = 14 * rank + ((tab >> (4 * e)) & 15);
                        mbar_wait(sb + SM_BAR + B_SEMPTY + slot * 8, ph);
                        const unsigned char* ap = g_H + (size_t)(gt * 28 + kb) * 16384;
                        if (lead) mbar_expect_tx(fb, 16384 + 8192 + 6144);
                        {
                            uint32_t tv = target + (lane >> 5);
                            asm volatile("{\n.reg .pred p;\n.reg .b32 c;\nSPIN_%=:\nmov.u32 c, %%clock;\nsub.u32 c, c, %0;\nsetp.lt.s32 p, c, 0;\n@p bra.uni SPIN_%=;\n}" ::"r"(tv) : "memory");
                        }
                        if (lead) {
                            bulk_g2s(da, ap, 16384, fb);
                            TR(164 + (p == 0 ? 0 : 2 + 4 * p) + i);
                            tma5d(db, &tm_w2, fb, 112 * pcol, 0, 0, 0, 2 * kb);
                            tma5d(db + 57344, &tm_w2b, fb, 112 * pcol + 64, 0, 0, 0, 2 * kb);
                        }
                        TRC(lead, 64 + 35 + (p == 0 ? 0 : 2 + 4 * p) + i);
                        target += TICK_F;
                        if (++e == cnt) e = 0;
                        if (++slot == S2_STAGES) { slot = 0; ph ^= 1; }
                    }
                }
                const int wcol = 112 * pcol + 48 * rank;
#pragma unroll 1
                for (uint32_t i = 0; i < 5; i++) {
                    const uint32_t sl = (i + 4) % S2_STAGES;
                    mbar_wait(sb + SM_BAR + B_WOFREE + i * 8, 0);
                    if (lead) {
                        tma2d(sb + SM_XN + (sl + 2) * 8192, &tm_wo, sb + SM_BAR + B_WOFULL + (i + 2) * 8, wcol, 64 * (i + 2));
                        if (i < 2) tma2d(sb + SM_XN + 57344 + (sl + 2) * 8192, &tm_wo, sb + SM_BAR + B_WOFULL + i * 8, wcol, 64 * i);
                    }
                }
            }
        } else if (warp == 17) {
            mbar_wait(sb + SM_BAR + B_XLD + 15 * 8, 0);
#pragma unroll 1
            for (uint32_t i = 0; i < 7; i++) {
                const uint32_t slot = i % KV_STAGES;
                const uint32_t fb = sb + SM_BAR + B_KVFULL + slot * 8;
                mbar_wait(sb + SM_BAR + B_KVEMPTY + slot * 8, ((i / KV_STAGES) & 1) ^ 1);
                if (lane == 0) {
                    mbar_expect_tx(fb, 8192);
                    tma2d(sb + SM_KV + slot * 8192, &tm_v, fb, qcol, 64 * i);
                }
            }
            uint32_t epoch;
            mbar_wait(sb + SM_BAR + B_EPOCH, 0);
            asm volatile("ld.shared.u32 %0, [%1];" : "=r"(epoch) : "r"(sb + SM_BAR + B_EPOCHVAL));
            mbar_wait(sb + SM_BAR + B_OWNKV, 0);
#pragma unroll 1
            for (uint32_t i = 0; i < 12; i++) {
                if (i == 1) {
                    if (lane < 2) flag_wait(&g_flagKV[(max(g - 1 - lane, 0) * 8 + j) * 8], epoch + 1);
                    __syncwarp();
                }
                const uint32_t hh = i >= 6 ? 1 : 0;
                const int b = (0x051234 >> (4 * (i - 6 * hh))) & 15;
                const int kbk = max(2 * g - 4 + b, 0);
                const uint32_t slot = (i + 7) % KV_STAGES;
                const uint32_t fb = sb + SM_BAR + B_KVFULL + slot * 8;
                mbar_wait(sb + SM_BAR + B_KVEMPTY + slot * 8, (((i + 7) / KV_STAGES) & 1) ^ 1);
                if (lane == 0) {
                    mbar_expect_tx(fb, 8192);
                    bulk_g2s(sb + SM_KV + slot * 8192, g_KV + (size_t)((2 * j + hh) * 32 + kbk) * 8192, 8192, fb);
                }
            }
        } else if (warp == 18) {
            uint32_t epoch = 0;
            if (lane == 0) {
                epoch = atomicAdd(&g_ticket, 1u) >> 7;
                asm volatile("st.shared.u32 [%0], %1;" ::"r"(sb + SM_BAR + B_EPOCHVAL), "r"(epoch) : "memory");
                mbar_arrive(sb + SM_BAR + B_EPOCH);
                if (rank == 0) {
                    const unsigned long long kv = ((unsigned long long)(epoch + 1) << 32) | key;
                    asm volatile("st.relaxed.gpu.global.u64 [%0], %1;" ::"l"(&g_key[cl]), "l"(kv) : "memory");
                }
            }
            __syncwarp();
            bar_sync(3, 288);
            if (lane == 0) {
                flag_set(&g_flagKV[(g * 8 + j) * 8], epoch + 1);
                mbar_arrive(sb + SM_BAR + B_OWNKV);
            }
            __syncwarp();
#pragma unroll 1
            for (int c = 2; c <= 4; c++) {
                bar_sync(2 + c, 288);
                TRC(lane == 0, 256 + 44 + 2 * c);
                if (lane == 0) flag_set(&g_flagH[(g * 8 + j) * 8], 4 * epoch + c);
                TRC(lane == 0, 256 + 45 + 2 * c);
                __syncwarp();
            }
        } else {
            if (lane == 0) {
                mbar_wait(sb + SM_BAR + B_XLD + 15 * 8, 0);
                const int b = blockIdx.x;
                l2_prefetch(reinterpret_cast<const char*>(P.w1) + (size_t)b * 12544, 12544);
                l2_prefetch(reinterpret_cast<const char*>(P.w3) + (size_t)b * 12544, 12544);
                l2_prefetch(reinterpret_cast<const char*>(P.w2) + (size_t)b * 12544, 12544);
                l2_prefetch(reinterpret_cast<const char*>(P.wo) + (size_t)b * 3136, 3136);
            }
            __syncwarp();
            uint32_t epoch;
            mbar_wait(sb + SM_BAR + B_EPOCH, 0);
            asm volatile("ld.shared.u32 %0, [%1];" : "=r"(epoch) : "r"(sb + SM_BAR + B_EPOCHVAL));
            unsigned long long k0, k1;
            const uint32_t t0 = (uint32_t)clock();
            while (true) {
                asm volatile("ld.relaxed.gpu.global.u64 %0, [%1];" : "=l"(k0) : "l"(&g_key[lane]) : "memory");
                asm volatile("ld.relaxed.gpu.global.u64 %0, [%1];" : "=l"(k1) : "l"(&g_key[lane + 32]) : "memory");
                const bool ok = (uint32_t)(k0 >> 32) == epoch + 1 && (uint32_t)(k1 >> 32) == epoch + 1;
                if (__all_sync(0xffffffffu, ok) || (uint32_t)clock() - t0 > WAIT_LIMIT) break;
                __nanosleep(100);
            }
            const uint32_t ref = __shfl_sync(0xffffffffu, (uint32_t)k0, 0);
            const int d0 = (int)((uint32_t)k0 - ref), d1 = (int)((uint32_t)k1 - ref);
            const int dm = __shfl_sync(0xffffffffu, cl < 32 ? d0 : d1, cl & 31);
            const int asg = __popc(__ballot_sync(0xffffffffu, d0 < dm || (d0 == dm && lane < cl))) +
                            __popc(__ballot_sync(0xffffffffu, d1 < dm || (d1 == dm && lane + 32 < cl)));
            if (lane == 0) {
                asm volatile("st.shared.u32 [%0], %1;" ::"r"(sb + SM_BAR + B_ASGVAL), "r"(asg) : "memory");
                mbar_arrive(sb + SM_BAR + B_ASG);
            }
            const int gt = asg >> 2;
#pragma unroll 1
            for (int c = 0; c < 3; c++) {
                if (lane < 4) flag_wait(&g_flagH[(gt * 8 + 4 * rank + lane) * 8], 4 * epoch + 2 + c);
                __syncwarp();
                if (lane == 0) {
                    mbar_arrive(sb + SM_BAR + B_FLG + c * 8);
                    TS(22 + c);
                }
            }
            {
                const uint32_t k = lane & 7;
                const unsigned char* op = g_O + (size_t)(gt * 7 + k) * 16384 + (k < 2 ? rank * 8192 : 0);
                const uint32_t dst = k < 2 ? sb + SM_XN + rank * 57344 + k * 8192 : sb + SM_WR + ((k + 2) % S2_STAGES) * 16384;
                const uint32_t frb = sb + SM_BAR + B_WOFREE + (k < 2 ? 0 : k - 2) * 8;
                bool todo = lane < 7 && (k < 2 || (k & 1) == (uint32_t)rank);
                uint32_t ok = 0;
                const unsigned int* fp = &g_flagO[(gt * 8 + k) * 8];
                mbar_wait(sb + SM_BAR + B_XBFREE, 0);
#pragma unroll 1
                for (int tries = 0; tries < 200000; tries++) {
                    if (ok != 0xff) {
                        uint32_t v = epoch + 1;
                        if (lane < 8 && !((ok >> k) & 1)) asm volatile("ld.acquire.gpu.global.u32 %0, [%1];" : "=r"(v) : "l"(fp) : "memory");
                        ok = __ballot_sync(0xffffffffu, (int)(v - (epoch + 1)) >= 0) & 0xff;
                    }
                    if (todo && ((ok >> k) & 3) == 3 && mbar_test(frb, 0)) {
                        bulk_g2s_mc(dst, op, k < 2 ? 8192 : 16384, sb + SM_BAR + B_WOFULL + k * 8);
                        TR(64 + 35 + 14 + k);
                        todo = false;
                    }
                    if (!__any_sync(0xffffffffu, todo)) break;
                    __nanosleep(ok == 0xff ? 30 : POLLNS);
                }
                TRC(lane == 0, 256 + 25);
            }
        }
        asm volatile("barrier.cluster.arrive.release.aligned;\nbarrier.cluster.wait.acquire.aligned;" ::: "memory");
        return;
    }

    {
        const uint32_t xw = sb + SM_XN + warp * 7168;
        const uint32_t xb = sb + SM_BAR + B_XLD + warp * 8;
        if (lane == 0) {
            mbar_init(xb, 1);
            fence_proxy_async_smem();
            mbar_expect_tx(xb, 7168);
            {
                const void* xp = P.x + (size_t)(g * 128 + warp * 8) * DM;
                asm volatile("" : "+l"(xp));
                const uint32_t tv = (((uint32_t)clock() + 40) | (XALIGN - 1)) + 1 + warp * 24;
                while ((int)((uint32_t)clock() - tv) < 0) {}
                bulk_g2s(xw, xp, 7168, xb);
            }
            if ((warp & 7) == 0) mbar_init(sb + SM_BAR + B_XRD + (warp >> 3) * 8, 8);
        }
        __syncwarp();
        bar_sync(11 + (warp >> 3), 256);
        TRC(tid == 0, 256 + 55);
        asm volatile("barrier.cluster.arrive.relaxed.aligned;" ::: "memory");
        mbar_wait(xb, 0);
        TRC(tid == 0, 256 + (40));
        TRC(tid == 256, 256 + (42));
        const int gq = lane >> 2;
        uint4 v[14];
        const uint32_t s0 = xw + gq * 896 + ((lane & 3) + ((gq & 1) ? 4 : 0)) * 16;
        const uint32_t s1 = xw + gq * 896 + ((lane & 3) + ((gq & 1) ? 0 : 4)) * 16;
#pragma unroll
        for (int i = 0; i < 14; i++) {
            asm volatile("ld.shared.v4.b32 {%0, %1, %2, %3}, [%4];"
                         : "=r"(v[i].x), "=r"(v[i].y), "=r"(v[i].z), "=r"(v[i].w)
                         : "r"(((i & 1) ? s1 : s0) + (i >> 1) * 128));
        }
        ln_process(v, sb + SM_XN + (warp >> 3) * 57344 + (warp & 7) * 1024, lane, sb + SM_BAR + B_XRD + (warp >> 3) * 8);
        fence_proxy_async_smem();
        TRC(tid == 0, 256 + (41));
        TRC(tid == 256, 256 + (43));
        asm volatile("barrier.cluster.wait.aligned;" ::: "memory");
    }

    if (wg >= 2) {
        asm volatile("setmaxnreg.inc.sync.aligned.u32 104;");
        bar_arrive(2, 384);
        attention_tile(3 - wg, sb, g, j, tid, warp & 3, lane);
        bar_sync(7, 256);
        if (tid == 384) {
            mbar_arrive_cluster(peer_sb + SM_BAR + B_XBFREE);
            uint32_t asg;
            mbar_wait(sb + SM_BAR + B_ASG, 0);
            asm volatile("ld.shared.u32 %0, [%1];" : "=r"(asg) : "r"(sb + SM_BAR + B_ASGVAL));
            mbar_expect_tx(sb + SM_BAR + B_XT, 16384);
            tma2d(sb + SM_KV + 16384, &tm_x, sb + SM_BAR + B_XT, (asg & 3) * 112 + rank * 48, (asg >> 2) * 128);
        }
        if (tid == 256) {
            TS(31);
            uint32_t epoch;
            mbar_wait(sb + SM_BAR + B_EPOCH, 0);
            asm volatile("ld.shared.u32 %0, [%1];" : "=r"(epoch) : "r"(sb + SM_BAR + B_EPOCHVAL));
            flag_set(&g_flagO[(g * 8 + j) * 8], epoch + 1);
            TS(29);
        }
        __syncwarp();
        asm volatile("barrier.cluster.arrive.relaxed.aligned;" ::: "memory");
    } else {
        asm volatile("setmaxnreg.inc.sync.aligned.u32 120;");
        const int w = wg;
        if (w == 0) {
            bar_sync(1, 256);
        } else {
            bar_arrive(1, 256);
            bar_sync(2, 384);
        }
        const bool elect = (tid & 127) == 0;
        const int wq = warp & 3;
        const int q = lane & 3;
        const int rloc0 = w * 64 + wq * 16 + (lane >> 2);
        const uint32_t alo = desc_lo(sb + SM_XN + w * 57344, 16);
        const uint32_t blo = desc_lo(sb + SM_WR, 4096);
        const uint32_t qlo = blo + (j & 1);
        const uint32_t mlo = desc_lo(sb + SM_WR, 2048);
        TRC(elect, 256 + (1 + w * 8));
        constexpr int GI = SW ? 1 : 0;
        unsigned char* const hbase = g_H + (size_t)g * 28 * 16384 + rloc0 * 128;
        uint32_t pk[32];
        auto epi_word = [&](int v) {
            const int s = v >> 2, i = v & 3;
            const int ga = 2 * (4 * (s >> 1) + i) + (s & 1);
            pk[ga] = hval2(pk[ga + 16 * GI], pk[ga + 16 * (1 - GI)]);
        };
        auto epi_store = [&](uint32_t hoff, uint32_t hsel, int s) {
            const int hf = s >> 1, rh = s & 1;
            stg128(hbase + hoff + rh * 1024 + (((4 * hf + hsel + q) ^ (rloc0 & 7)) << 4), pk[8 * hf + rh], pk[8 * hf + 2 + rh],
                   pk[8 * hf + 4 + rh], pk[8 * hf + 6 + rh]);
        };
        WState ws = {0, 0, 0};
        mbar_wait(sb + SM_BAR + B_WFULL, 0);
        gemm1_chunk<false, 1>(pk, ws, sb, alo, qlo, mlo, elect, peer_sb, [&](int s) {
            if (s > 0) bar_arrive(8 + w, 256);
        });
        TRC(elect, 256 + (2 + w * 8));
        gemm1_chunk<true, 1>(pk, ws, sb, alo, qlo, mlo, elect, peer_sb, [&](int) {
            unsigned char* const kbase = g_KV + ((size_t)(2 * j) * 32 + 2 * g + w) * 8192 + (rloc0 & 63) * 64 + ((q ^ ((rloc0 >> 1) & 3)) << 4);
#pragma unroll
            for (int rh = 0; rh < 2; rh++) {
                stg128(kbase + rh * 512, pk[rh], pk[2 + rh], pk[4 + rh], pk[6 + rh]);
                stg128(kbase + rh * 512 + 32 * 8192, pk[6 + rh], pk[8 + rh], pk[10 + rh], pk[12 + rh]);
                stg128(kbase + rh * 512 + 4096, pk[16 + rh], pk[18 + rh], pk[20 + rh], q < 2 ? pk[22 + rh] : (q == 2 ? 0x00003f80u : 0u));
                stg128(kbase + rh * 512 + 4096 + 32 * 8192, q >= 2 ? pk[22 + rh] : (q == 0 ? 0x00003f80u : 0u), pk[24 + rh], pk[26 + rh], pk[28 + rh]);
            }
            bar_arrive(3, 288);
        });
        TRC(elect, 256 + (3 + w * 8));
        uint32_t hoff = (fm >> 6) * 16384, hsel = 4 * ((fm >> 5) & 1) - 4;
#pragma unroll 1
        for (int c = 0; c < 3; c++) {
            gemm1_chunk<false, 7>(pk, ws, sb, alo, blo, mlo, elect, peer_sb, [&](int s) {
                if (s < 4 && (s >= 2 || c > 0)) {
#pragma unroll
                    for (int v = 4 * s; v < 4 * s + 4; v++) epi_word(v);
                    epi_store(hoff, hsel, s);
                }
                if (s == 3 && c > 0) bar_arrive(3 + c, 288);
                if (s == 6 && c == 1) bar_sync(13 + w, 256);
            });
            hoff = ((fa >> 6) + c) * 16384;
            hsel = 0;
        }
        TRC(elect, 256 + (4 + w * 8));
        float f[56];
        const uint32_t a2lo = desc_lo(sb + SM_WR + w * 8192, 16);
        const uint32_t b2lo = desc_lo(sb + SM_XN + 2 * 8192, 57344);
#pragma unroll
        for (int n = 0; n < EPI2; n++) {
            if (n > 0) {
                mbar_wait(sb + SM_BAR + B_SFULL + n * 8, 0);
                wg_wait<0>();
            }
            wg_fence();
#pragma unroll
            for (int k = 0; k < 4; k++) {
                if ((n | k) == 0) wgmma_ssz_n112<1>(f, a2lo, 0, HI_128, b2lo, 0, HI_128);
                else wgmma_ss_n112<1>(f, a2lo, n * 1024 + k * 2, HI_128, b2lo, n * 512 + k * 128, HI_128, 1);
            }
            wg_commit();
            TRC(tid == 0, 35 + n);
            if (n == 0) w_release_prev(ws, sb, peer_sb, elect);
            else if (elect) mbar_arrive(sb + SM_BAR + B_SEMPTY + (n - 1) * 8);
#pragma unroll
            for (int v = (16 / EPI2) * n; v < (16 / EPI2) * (n + 1); v++) {
                epi_word(v);
                if ((v & 3) == 3) epi_store(hoff, 0, v >> 2);
            }
        }
        bar_arrive(6, 288);
        uint32_t asg;
        mbar_wait(sb + SM_BAR + B_ASG, 0);
        asm volatile("ld.shared.u32 %0, [%1];" : "=r"(asg) : "r"(sb + SM_BAR + B_ASGVAL));
        const size_t off0 = (size_t)((asg >> 2) * 128 + rloc0) * DM + (asg & 3) * 112 + rank * 56 + 2 * q;
        uint32_t slot = EPI2, ph = 0;
#pragma unroll 1
        for (int n = EPI2; n < 14; n++) {
            wg_wait<0>();
            if (elect) {
                if (n < 10) {
                    mbar_arrive(sb + SM_BAR + B_SEMPTY + (slot == 0 ? S2_STAGES - 1 : slot - 1) * 8);
                } else {
                    mbar_arrive(sb + SM_BAR + B_WOFREE + (n - 10) * 8);
                    mbar_arrive_cluster(peer_sb + SM_BAR + B_WOFREE + (n - 10) * 8);
                }
            }
            mbar_wait(sb + SM_BAR + B_SFULL + slot * 8, ph);
            wg_fence();
            const uint32_t ad = a2lo + slot * 1024, bd = b2lo + slot * 512;
#pragma unroll
            for (int k = 0; k < 4; k++) wgmma_ss_n112<1>(f, ad, k * 2, HI_128, bd, k * 128, HI_128, 1);
            wg_commit();
            TRC(tid == 0, 35 + n);
            if (++slot == S2_STAGES) { slot = 0; ph ^= 1; }
        }
        wg_wait<0>();
        fence_regs(f);
        if (elect) {
            mbar_arrive(sb + SM_BAR + B_WOFREE + 32);
            mbar_arrive_cluster(peer_sb + SM_BAR + B_WOFREE + 32);
            TS(6 + w * 8);
        }
        final_phase(f, off0, sb, peer_sb, tid, w, P, rank, rloc0, q);
        TRC(elect, 256 + (7 + w * 8));
    }
}

typedef CUresult (*EncFn)(CUtensorMap*, CUtensorMapDataType, cuuint32_t, void*, const cuuint64_t*, const cuuint64_t*,
                          const cuuint32_t*, const cuuint32_t*, CUtensorMapInterleave, CUtensorMapSwizzle,
                          CUtensorMapL2promotion, CUtensorMapFloatOOBfill);

struct HostState {
    bool init;
    const void* ptrs[7];
    CUtensorMap qk, v, w13, w13m, w2, w2b, wo, x;
    int swap13;
};
HostState g_hs;

bool encode(EncFn enc, CUtensorMap* m, int rank, const void* base, const cuuint64_t* dims, const cuuint64_t* strides,
            const cuuint32_t* box, CUtensorMapSwizzle swz = CU_TENSOR_MAP_SWIZZLE_128B) {
    cuuint32_t es[5] = {1, 1, 1, 1, 1};
    return enc(m, CU_TENSOR_MAP_DATA_TYPE_BFLOAT16, rank, const_cast<void*>(base), dims, strides, box, es,
               CU_TENSOR_MAP_INTERLEAVE_NONE, swz, CU_TENSOR_MAP_L2_PROMOTION_L2_128B,
               CU_TENSOR_MAP_FLOAT_OOB_FILL_NONE) == CUDA_SUCCESS;
}

}

extern "C" void kernel_launch(void* const* d_in, const int* in_sizes, int n_in, void* d_out, int out_size) {
    (void)in_sizes; (void)n_in; (void)out_size;
    const __nv_bfloat16* x = (const __nv_bfloat16*)d_in[0];
    const __nv_bfloat16* wqkv = (const __nv_bfloat16*)d_in[1];
    const __nv_bfloat16* wo = (const __nv_bfloat16*)d_in[2];
    const __nv_bfloat16* w1 = (const __nv_bfloat16*)d_in[4];
    const __nv_bfloat16* w3 = (const __nv_bfloat16*)d_in[5];
    const __nv_bfloat16* w2 = (const __nv_bfloat16*)d_in[6];

    HostState& hs = g_hs;
    bool same = hs.init;
    for (int i = 0; i < 7 && same; i++) same = (hs.ptrs[i] == d_in[i]);
    if (!same) {
        EncFn enc = nullptr;
        cudaDriverEntryPointQueryResult qr;
        cudaGetDriverEntryPoint("cuTensorMapEncodeTiled", (void**)&enc, cudaEnableDefault, &qr);
        if (!enc) return;
        bool ok = true;
        {
            cuuint64_t d[3] = {448, 448, 3}, s[2] = {2688, 896};
            cuuint32_t b[3] = {64, 32, 2};
            ok &= encode(enc, &hs.qk, 3, wqkv, d, s, b);
            cuuint32_t b1[2] = {64, 64};
            ok &= encode(enc, &hs.v, 2, wqkv, d, s, b1);
        }
        const bool swap = (const char*)w3 < (const char*)w1;
        const __nv_bfloat16* wlo = swap ? w3 : w1;
        const cuuint64_t delta = swap ? (cuuint64_t)((const char*)w1 - (const char*)w3) : (cuuint64_t)((const char*)w3 - (const char*)w1);
        hs.swap13 = swap ? 1 : 0;
        {
            cuuint64_t d[3] = {1792, 448, 2}, s[2] = {3584, delta};
            cuuint32_t b[3] = {64, 32, 2};
            ok &= encode(enc, &hs.w13, 3, wlo, d, s, b);
        }
        {
            cuuint64_t d[3] = {1792, 448, 2}, s[2] = {3584, delta};
            cuuint32_t b[3] = {32, 32, 2};
            ok &= encode(enc, &hs.w13m, 3, wlo, d, s, b, CU_TENSOR_MAP_SWIZZLE_64B);
        }
        {
            cuuint64_t d[5] = {448, 2, 4, 4, 56}, s[4] = {896, 8 * 896, 2 * 896, 32 * 896};
            cuuint32_t b[5] = {64, 2, 4, 4, 2};
            ok &= encode(enc, &hs.w2, 5, w2, d, s, b);
            cuuint32_t b2[5] = {48, 2, 4, 4, 2};
            ok &= encode(enc, &hs.w2b, 5, w2, d, s, b2);
        }
        {
            cuuint64_t d[2] = {448, 448}, s[1] = {896};
            cuuint32_t b[2] = {64, 64};
            ok &= encode(enc, &hs.wo, 2, wo, d, s, b);
            cuuint64_t dx[2] = {448, 2048};
            cuuint32_t bx[2] = {64, 128};
            ok &= encode(enc, &hs.x, 2, x, dx, s, bx);
        }
        if (!ok) return;
        cudaFuncSetAttribute(fused_kernel<false>, cudaFuncAttributeMaxDynamicSharedMemorySize, SM_TOTAL + SM_DBG);
        cudaFuncSetAttribute(fused_kernel<true>, cudaFuncAttributeMaxDynamicSharedMemorySize, SM_TOTAL + SM_DBG);
        for (int i = 0; i < 7; i++) hs.ptrs[i] = d_in[i];
        hs.init = true;
    }
    Params P;
    P.x = x; P.wqkv = wqkv; P.w1 = w1; P.w3 = w3; P.w2 = w2; P.wo = wo;
    P.out = (__nv_bfloat16*)d_out;
    P.swap13 = hs.swap13;
    if (hs.swap13) fused_kernel<true><<<128, NTHREADS, SM_TOTAL + SM_DBG>>>(hs.qk, hs.v, hs.w13, hs.w13m, hs.w2, hs.w2b, hs.wo, hs.x, P);
    else fused_kernel<false><<<128, NTHREADS, SM_TOTAL + SM_DBG>>>(hs.qk, hs.v, hs.w13, hs.w13m, hs.w2, hs.w2b, hs.wo, hs.x, P);
}
```
